```python
import torch

def _softmax(x, axis=-1):
    return torch.softmax(x, dim=axis)
def _gelu(x):
    return torch.nn.functional.gelu(x, approximate="tanh")
def _silu(x):
    return torch.nn.functional.silu(x)
def _sigmoid(x):
    return torch.sigmoid(x)
def _layernorm(x, axis=-1, eps=1e-5):
    m = x.mean(dim=axis, keepdim=True)
    v = x.var(dim=axis, keepdim=True, unbiased=False)
    return (x - m) / torch.sqrt(v + eps)
def _scatter_add(tgt, idx, src, axis=0):
    return tgt.clone().index_add_(axis, idx, src)
def _segment_sum(src, seg, n):
    out = torch.zeros((n,) + src.shape[1:], dtype=src.dtype)
    return out.index_add_(0, seg, src)
def _pad(x, pw):
    flat = tuple(v for pair in reversed(pw) for v in pair)
    return torch.nn.functional.pad(x, flat)

kernel_name = 'recurrent_scan__spectral_gfnet__swiglu_ffn__prompt'

def setup_inputs():

    _w = (lambda a: (lambda t: t.to(torch.bfloat16) if t.is_floating_point() else t)(torch.as_tensor(a)))
    def _A_setup():
        B, S, D = 1, 2048, 1024
        Df = D // 2 + 1
        return {
            "x": _w((lambda *s: torch.randn(*s, dtype=torch.bfloat16) * 0.05)(B, S, D)),
            "w_r": _w((lambda *s: torch.randn(*s, dtype=torch.bfloat16) * 0.05)(S, Df) * 0.02),
            "w_i": _w((lambda *s: torch.randn(*s, dtype=torch.bfloat16) * 0.05)(S, Df) * 0.02),
        }
    _A_in = _A_setup()

    def _B_setup():
        B, S, D, F = 1, 2048, 1024, 3584
        return {
            "x": _w((lambda *s: torch.randn(*s, dtype=torch.bfloat16) * 0.05)(B, S, D)),
            "w_gate": _w((lambda *s: torch.randn(*s, dtype=torch.bfloat16) * 0.05)(D, F)),
            "w_up": _w((lambda *s: torch.randn(*s, dtype=torch.bfloat16) * 0.05)(D, F)),
            "w_down": _w((lambda *s: torch.randn(*s, dtype=torch.bfloat16) * 0.05)(F, D)),
        }
    _B_in = _B_setup()

    return {
        "A_x": _A_in["x"],
        "A_w_r": _A_in["w_r"],
        "A_w_i": _A_in["w_i"],
        "B_x": _B_in["x"],
        "B_w_gate": _B_in["w_gate"],
        "B_w_up": _B_in["w_up"],
        "B_w_down": _B_in["w_down"],
    }

def reference(A_x, A_w_r, A_w_i, B_x, B_w_gate, B_w_up, B_w_down):
    def _A_ref(x, w_r, w_i):
        B, S, D = x.shape
        X = (lambda x, axes=(-2,-1): torch.fft.rfft2(x.float(), dim=axes))(x, axes=(-2, -1))
        W = w_r + 1j * w_i
        X = X * W
        y = (lambda x, s, axes=(-2,-1): torch.fft.irfft2(x, s=s, dim=axes).to(torch.bfloat16))(X, (S, D), axes=(-2, -1))
        return y

    def _B_ref(x, w_gate, w_up, w_down):
        g = _silu(x @ w_gate)
        u = x @ w_up
        return (g * u) @ w_down

    x = A_x
    xn = _layernorm(x, axis=-1)
    s = _A_ref(xn, A_w_r, A_w_i)
    g = _silu(_B_ref(xn, B_w_gate, B_w_up, B_w_down))
    return x + s * g
```

```cpp
#include <cuda_runtime.h>
#include <cuda.h>
#include <cuda_bf16.h>
#include <cuda_fp16.h>
#include <stdint.h>

constexpr int TAB_A1 = 0;
constexpr int TAB_T1 = 4;
constexpr int TAB_B1 = 8;
constexpr int TAB_G1 = 12;
constexpr int TAB_B2 = 16;
constexpr int TAB_A3 = 20;
constexpr int TAB_A2_0 = 24;
constexpr int TAB_T2_0 = 28;
constexpr int TAB_T3_0 = 36;
constexpr int TAB_B4_0 = 44;
constexpr int TAB_A5 = 72;
constexpr int TAB_T5 = 78;
constexpr int TAB_A6 = 82;
constexpr int TAB_A7 = 86;
constexpr int TAB_PAR_STRIDE = 24;
__device__ const __align__(128) unsigned int g_tab[11520] = {
0x31a831a8,0x31a831a8,0x31a831a8,0x31a831a8,0x31a831a8,0x0,0x31a831a8,0x80000000,0x31a831a8,0xb1a8b1a8,0x31a831a8,0xb1a8b1a8,0x31a831a8,0x80008000,0x31a831a8,0x80008000,
0x300031a8,0x300031a8,0xb0000000,0xb0000000,0x2e49318c,0xb0b4a86a,0xb0b4a86a,0xae49b18c,0x2c54313a,0xac54b13a,0xb13aac54,0x313a2c54,0x286a30b4,0x318c2e49,0xb18cae49,0x286a30b4,
0x31a8,0x31a8,0x8000b1a8,0x8000b1a8,0xac54313a,0xb13aac54,0x2c54b13a,0x313a2c54,0xb0003000,0x3000b000,0x3000b000,0xb0003000,0xb13a2c54,0x2c54313a,0x313aac54,0xac54b13a,
0xb00031a8,0xb00031a8,0x30008000,0x30008000,0xb18c30b4,0xa86aae49,0x286a2e49,0xb18c30b4,0xb13a2c54,0x313aac54,0xac54313a,0x2c54b13a,0xae49a86a,0xb0b4318c,0xb0b4318c,0x2e49286a,
0xb1a831a8,0xb1a831a8,0xb1a831a8,0xb1a831a8,0xb0003000,0x3000b000,0xb0003000,0x3000b000,0x80000000,0x8000,0x80000000,0x80008000,0x3000b000,0xb0003000,0x3000b000,0xb0003000,
0xb00031a8,0xb00031a8,0x30000000,0x30008000,0x286a2e49,0x318cb0b4,0x318cb0b4,0xa86aae49,0x313aac54,0xb13a2c54,0x2c54b13a,0xac54313a,0x30b4b18c,0x2e49286a,0xae49a86a,0x30b4b18c,
0x800031a8,0x800031a8,0xb1a8,0x8000b1a8,0x313a2c54,0x2c54b13a,0xb13aac54,0xac54313a,0x3000b000,0xb0003000,0xb0003000,0x3000b000,0xac54b13a,0x313aac54,0x2c54313a,0xb13a2c54,
0x300031a8,0x300031a8,0xb0008000,0xb0008000,0x30b4286a,0xae49b18c,0x2e49318c,0x30b4286a,0xac54b13a,0x2c54313a,0x313a2c54,0xb13aac54,0xb18cae49,0xa86ab0b4,0xa86ab0b4,0x318c2e49,
0x31a831a8,0x31a831a8,0x31a831a8,0x31a831a8,0x31a831a8,0x80008000,0x31a831a8,0x80008000,0x31a831a8,0xb1a8b1a8,0x31a831a8,0xb1a8b1a8,0x31a831a8,0x80008000,0x31a831a8,0x80008000,
0xb000b1a8,0xb000b1a8,0x30008000,0x30008000,0xae49b18c,0x30b4286a,0x30b4286a,0x2e49318c,0xac54b13a,0x2c54313a,0x313a2c54,0xb13aac54,0xa86ab0b4,0xb18cae49,0x318c2e49,0xa86ab0b4,
0x31a8,0x800031a8,0x8000b1a8,0x8000b1a8,0xac54313a,0xb13aac54,0x2c54b13a,0x313a2c54,0xb0003000,0x3000b000,0x3000b000,0xb0003000,0xb13a2c54,0x2c54313a,0x313aac54,0xac54b13a,
0x3000b1a8,0x3000b1a8,0xb0000000,0xb0000000,0x318cb0b4,0x286a2e49,0xa86aae49,0x318cb0b4,0x313aac54,0xb13a2c54,0x2c54b13a,0xac54313a,0x2e49286a,0x30b4b18c,0x30b4b18c,0xae49a86a,
0xb1a831a8,0xb1a831a8,0xb1a831a8,0xb1a831a8,0xb0003000,0x3000b000,0xb0003000,0x3000b000,0x80000000,0x8000,0x80008000,0x8000,0x3000b000,0xb0003000,0x3000b000,0xb0003000,
0x3000b1a8,0x3000b1a8,0xb0008000,0xb0008000,0xa86aae49,0xb18c30b4,0xb18c30b4,0x286a2e49,0xb13a2c54,0x313aac54,0xac54313a,0x2c54b13a,0xb0b4318c,0xae49a86a,0x2e49286a,0xb0b4318c,
0x800031a8,0x800031a8,0x8000b1a8,0xb1a8,0x313a2c54,0x2c54b13a,0xb13aac54,0xac54313a,0x3000b000,0xb0003000,0xb0003000,0x3000b000,0xac54b13a,0x313aac54,0x2c54313a,0xb13a2c54,
0xb000b1a8,0xb000b1a8,0x30008000,0x30000000,0xb0b4a86a,0x2e49318c,0xae49b18c,0xb0b4a86a,0x2c54313a,0xac54b13a,0xb13aac54,0x313a2c54,0x318c2e49,0x286a30b4,0x286a30b4,0xb18cae49,
0x31a831a8,0x8000,0x31a831a8,0x0,0xb1a8b1a8,0xb1a8b1a8,0xb1a8b1a8,0xb1a8b1a8,0x31a831a8,0x80008000,0x31a831a8,0x80008000,0xb1a8b1a8,0x31a831a8,0xb1a8b1a8,0x31a831a8,
0xb0008000,0xb0008000,0xb000b1a8,0xb000b1a8,0xb0b4a86a,0xae49b18c,0xae49b18c,0x30b4286a,0xb13aac54,0x313a2c54,0xac54b13a,0x2c54313a,0xb18cae49,0x286a30b4,0xa86ab0b4,0xb18cae49,
0xb1a88000,0xb1a88000,0x31a88000,0x31a88000,0xb13aac54,0x2c54b13a,0x313a2c54,0xac54313a,0xb000b000,0x30003000,0x30003000,0xb000b000,0xac54b13a,0xb13a2c54,0x2c54313a,0x313aac54,
0xb0008000,0xb0008000,0xb00031a8,0xb00031a8,0xa86aae49,0x318cb0b4,0xb18c30b4,0xa86aae49,0x2c54b13a,0xac54313a,0xb13a2c54,0x313aac54,0x30b4b18c,0xae49a86a,0xae49a86a,0xb0b4318c,
0x80008000,0x80008000,0x80000000,0x80000000,0x3000b000,0x3000b000,0x3000b000,0x3000b000,0x31a8b1a8,0xb1a831a8,0x31a8b1a8,0xb1a831a8,0x3000b000,0x3000b000,0x3000b000,0x3000b000,
0x30008000,0x30008000,0x3000b1a8,0x3000b1a8,0x318cb0b4,0xa86aae49,0xa86aae49,0xb18c30b4,0x2c54b13a,0xac54313a,0xb13a2c54,0x313aac54,0xae49a86a,0x30b4b18c,0xb0b4318c,0xae49a86a,
0x31a88000,0x31a88000,0xb1a88000,0xb1a88000,0x2c54b13a,0xb13aac54,0xac54313a,0x313a2c54,0xb000b000,0x30003000,0x30003000,0xb000b000,0xb13a2c54,0xac54b13a,0x313aac54,0x2c54313a,
0x30008000,0x30008000,0x300031a8,0x300031a8,0xae49b18c,0xb0b4a86a,0x30b4286a,0xae49b18c,0xb13aac54,0x313a2c54,0xac54b13a,0x2c54313a,0x286a30b4,0xb18cae49,0xb18cae49,0xa86ab0b4,
0x31a831a8,0x0,0x31a831a8,0x0,0xb1a8b1a8,0xb1a8b1a8,0xb1a8b1a8,0xb1a8b1a8,0x31a831a8,0x80008000,0x31a831a8,0x80000000,0xb1a8b1a8,0x31a831a8,0xb1a8b1a8,0x31a831a8,
0x30008000,0x30008000,0x300031a8,0x300031a8,0x30b4286a,0x2e49318c,0x2e49318c,0xb0b4a86a,0x313a2c54,0xb13aac54,0x2c54313a,0xac54b13a,0x318c2e49,0xa86ab0b4,0x286a30b4,0x318c2e49,
0xb1a80000,0xb1a80000,0x31a88000,0x31a88000,0xb13aac54,0x2c54b13a,0x313a2c54,0xac54313a,0xb000b000,0x30003000,0x30003000,0xb000b000,0xac54b13a,0xb13a2c54,0x2c54313a,0x313aac54,
0x30008000,0x30008000,0x3000b1a8,0x3000b1a8,0x286a2e49,0xb18c30b4,0x318cb0b4,0x286a2e49,0xac54313a,0x2c54b13a,0x313aac54,0xb13a2c54,0xb0b4318c,0x2e49286a,0x2e49286a,0x30b4b18c,
0x80000000,0x80000000,0x80000000,0x0,0x3000b000,0x3000b000,0x3000b000,0x3000b000,0x31a8b1a8,0xb1a831a8,0x31a8b1a8,0xb1a831a8,0x3000b000,0x3000b000,0x3000b000,0x3000b000,
0xb0008000,0xb0000000,0xb00031a8,0xb00031a8,0xb18c30b4,0x286a2e49,0x286a2e49,0x318cb0b4,0xac54313a,0x2c54b13a,0x313aac54,0xb13a2c54,0x2e49286a,0xb0b4318c,0x30b4b18c,0x2e49286a,
0x31a80000,0x31a80000,0xb1a88000,0xb1a80000,0x2c54b13a,0xb13aac54,0xac54313a,0x313a2c54,0xb000b000,0x30003000,0x30003000,0xb000b000,0xb13a2c54,0xac54b13a,0x313aac54,0x2c54313a,
0xb0008000,0xb0008000,0xb000b1a8,0xb000b1a8,0x2e49318c,0x30b4286a,0xb0b4a86a,0x2e49318c,0x313a2c54,0xb13aac54,0x2c54313a,0xac54b13a,0xa86ab0b4,0x318c2e49,0x318c2e49,0x286a30b4,
0x3b3b3bfe,0x36d72a48,0x3bc33bfe,0x33c62a48,0x3564395f,0x3b8839ed,0x3a6d3b3b,0x38c436d7,0xb6d7aa48,0x3b3b3bfe,0x381d395f,0x3add39ed,0xbb88b9ed,0x3564395f,0x30b23564,0x3bea3b88,
0x3b503bfe,0x367c2a48,0x3bce3bfe,0x33032a48,0x367c39a8,0x3b5039a8,0x3ac23b64,0x3848361f,0xb5052a48,0x3b993bfe,0x38ec39ed,0x3a4f395f,0xbaf6b913,0x37e33a2f,0x3505378b,0x3b993b0e,
0x3b643bfe,0x361f2a48,0x3bd93bfe,0x323e2a48,0x378b39ed,0x3b0e395f,0x3b0e3b88,0x378b3564,0xb23e30b2,0x3bd93bea,0x39a83a6d,0x39a838c4,0xba2fb81d,0x39133add,0x378b38c4,0x3b0e3a6d,
0x3b773bfe,0x35c22a48,0x3be23bfe,0x31792a48,0x38483a2f,0x3ac23913,0x3b503ba8,0x367c34a5,0xacb533c6,0x3bfa3bc3,0x3a4f3add,0x38ec381d,0xb93ab61f,0x3a0f3b64,0x38ec39a8,0x3a4f39a8,
0x3b883bfe,0x35642a48,0x3bea3bfe,0x30b22a48,0x38c43a6d,0x3a6d38c4,0x3b883bc3,0x356433c6,0x2a483564,0x3bfe3b88,0x3add3b3b,0x381d36d7,0xb81db3c6,0x3add3bc3,0x39ed3a6d,0x395f38c4,
0x3b993bfe,0x35052a48,0x3bf13bfe,0x2fd62a48,0x393a3aa7,0x3a0f3872,0x3bb63bd9,0x3444323e,0x317936d7,0x3be23b3b,0x3b503b88,0x367c3564,0xb5c2ae46,0x3b773bf6,0x3ac23b0e,0x3848378b,
0x3ba83bfe,0x34a52a48,0x3bf63bfe,0x2e462a48,0x39a83add,0x39a8381d,0x3bd93bea,0x323e30b2,0x34a5381d,0x3ba83add,0x3ba83bc3,0x34a533c6,0xb23e2a48,0x3bd93bfe,0x3b643b88,0x361f3564,
0x3bb63bfe,0x34442a48,0x3bfa3bfe,0x2cb52a48,0x3a0f3b0e,0x393a378b,0x3bf13bf6,0x2fd62e46,0x367c38c4,0x3b503a6d,0x3be23bea,0x317930b2,0xa648323e,0x3bff3bd9,0x3bce3bd9,0x3303323e,
0x3add3bea,0x381d30b2,0x3ba83bf6,0x34a52e46,0x33c638c4,0x3bc33a6d,0x3a2f3b0e,0x3913378b,0xb81db0b2,0x3add3bea,0x378b3913,0x3b0e3a2f,0xbbc3ba6d,0x33c638c4,0x2e4634a5,0x3bf63ba8,
0x3afc3bec,0x37cd3080,0x3bb93bf7,0x342c2de2,0x351d391d,0x3b953a27,0x3a923b41,0x389136c1,0xb665a97f,0x3b553bfe,0x38a639b1,0x3a83399f,0xbb4bb99f,0x369339b1,0x345d36ee,0x3bb23b36,
0x3b1a3bed,0x375e304e,0x3bc93bf8,0x33652d7e,0x364e3972,0x3b5a39dc,0x3ae93b6e,0x380735f1,0xb4752bd9,0x3baf3bfc,0x39723a3f,0x39dc3900,0xba99b8b0,0x38873a7c,0x37053887,0x3b303a99,
0x3b363bef,0x36ee301d,0x3bd63bf9,0x326f2d1a,0x377539c3,0x3b14398d,0x3b363b95,0x36ee351d,0xb0e43147,0x3be83be4,0x3a273abc,0x391d3852,0xb9b1b748,0x399f3b20,0x38ba397b,0x3a7439d4,
0x3b503bf1,0x367c2fd6,0x3be23bfa,0x31792cb5,0x38483a0f,0x3ac2393a,0x3b773bb6,0x35c23444,0xa6483444,0x3bff3bb6,0x3ac23b25,0x38483732,0xb89bb505,0x3a8a3b99,0x39cb3a4f,0x398438ec,
0x3b693bf2,0x36082f72,0x3bec3bfb,0x30802c51,0x38ce3a56,0x3a6538e2,0x3bab3bd1,0x348d32d2,0x2eaa35da,0x3bf53b72,0x3b413b7b,0x36c135ab,0xb6c1b147,0x3b413be4,0x3aae3afc,0x386737cd,
0x3b803bf4,0x35932f0e,0x3bf43bfc,0x2f0e2bd9,0x394d3a99,0x39fe3887,0x3bd43be6,0x32a13115,0x3365375e,0x3bc93b1a,0x3ba03bbc,0x34d53414,0xb414a248,0x3bbc3c00,0x3b5a3b80,0x364e3593,
0x3b953bf5,0x351d2eaa,0x3bf93bfd,0x2d1a2b11,0x39c33ad6,0x398d3828,0x3bef3bf5,0x301d2eaa,0x35ab3867,0x3b7b3aae,0x3be03be8,0x31aa30e4,0xad1a3080,0x3bf93bec,0x3bcb3bd6,0x3334326f,
0x3a6d3bc3,0x38c433c6,0x3b883bea,0x356430b2,0x30b2381d,0x3bea3add,0x39ed3add,0x395f381d,0xb8c4b3c6,0x3a6d3bc3,0x36d738c4,0x3b3b3a6d,0xbbeabadd,0x30b2381d,0x2a4833c6,0x3bfe3bc3,
0x3a993bc9,0x38873365,0x3ba03bed,0x34d5304e,0x33653887,0x3bc93a99,0x3a5e3b1a,0x38d8375e,0xb7b7b04e,0x3b023bed,0x385d3972,0x3ab539dc,0xbb91ba1f,0x35343927,0x3365364e,0x3bc93b5a,
0x3ac23bce,0x38483303,0x3bb63bf1,0x34442fd6,0x350538ec,0x3b993a4f,0x3ac23b50,0x3848367c,0xb5c2a648,0x3b773bff,0x393a3a0f,0x3a0f393a,0xbaf6b93a,0x37e33a0f,0x367c3848,0x3b503ac2,
0x3ae93bd4,0x380732a1,0x3bc93bf4,0x33652f0e,0x364e394d,0x3b5a39fe,0x3b1a3b80,0x375e3593,0xb3652d7e,0x3bc93bf8,0x39fe3a99,0x394d3887,0xba1fb832,0x39273ad0,0x3887394d,0x3a9939fe,
0x3b0e3bd9,0x378b323e,0x3bd93bf6,0x323e2e46,0x378b39a8,0x3b0e39a8,0x3b643ba8,0x361f34a5,0xae46323e,0x3bf63bd9,0x3aa73b0e,0x3872378b,0xb913b61f,0x3a2f3b64,0x39a83a2f,0x39a83913,
0x3b303bdd,0x370531db,0x3be63bf8,0x31152d7e,0x385d39fe,0x3ab5394d,0x3ba03bc9,0x34d53365,0x28b634d5,0x3bff3ba0,0x3b303b6e,0x370535f1,0xb7b7b365,0x3b023bc9,0x3a993ae9,0x38873807,
0x3b503be2,0x367c3179,0x3bf13bfa,0x2fd62cb5,0x38ec3a4f,0x3a4f38ec,0x3bce3be2,0x33033179,0x3179367c,0x3be23b50,0x3b993bb6,0x35053444,0xb505acb5,0x3b993bfa,0x3b503b77,0x367c35c2,
0x3b6e3be6,0x35f13115,0x3bf83bfc,0x2d7e2bd9,0x39723a99,0x39dc3887,0x3bed3bf4,0x304e2f0e,0x34d53807,0x3ba03ae9,0x3bdd3be6,0x31db3115,0xb04e2d7e,0x3bed3bf8,0x3bc93bd4,0x336532a1,
0x39ed3b88,0x395f3564,0x3b643bd9,0x361f323e,0x2a4836d7,0x3bfe3b3b,0x39a83aa7,0x39a83872,0xb95fb564,0x39ed3b88,0x361f3872,0x3b643aa7,0xbbfebb3b,0x2a4836d7,0x323e,0x3c003bd9,
0x3a273b95,0x391d351d,0x3b843be0,0x357c31aa,0x308037cd,0x3bec3afc,0x3a273af0,0x391d37f9,0xb87cb334,0x3aa03bcb,0x38123930,0x3ae33a17,0xbbc6ba92,0x33963891,0x320d35ab,0x3bdb3b7b,
0x3a5e3ba0,0x38d834d5,0x3ba03be6,0x34d53115,0x3365385d,0x3bc93ab5,0x3a993b30,0x38873705,0xb705af0e,0x3b303bf4,0x390039dc,0x3a3f3972,0xbb46b9ba,0x36aa3996,0x35f13807,0x3b6e3ae9,
0x3a923bab,0x3891348d,0x3bb93bec,0x342c3080,0x351d38ce,0x3b953a65,0x3afc3b69,0x37cd3608,0xb4ed1e48,0x3b9d3c00,0x39d43a74,0x397b38ba,0xba83b8ba,0x38a63a74,0x3852391d,0x3abc3a27,
0x3ac23bb6,0x38483444,0x3bce3bf1,0x33032fd6,0x367c393a,0x3b503a0f,0x3b503b99,0x367c3505,0xb1792fd6,0x3be23bf1,0x3a8a3af6,0x389b37e3,0xb984b732,0x39cb3b25,0x39843a0f,0x39cb393a,
0x3af03bc0,0x37f933f7,0x3be03bf5,0x31aa2eaa,0x37cd399f,0x3afc39b1,0x3b953bc0,0x351d33f7,0xa7da3396,0x3bff3bc6,0x3b203b5f,0x37483637,0xb852b4bd,0x3abc3ba4,0x3a833ad6,0x38a63828,
0x3b1a3bc9,0x375e3365,0x3bed3bf8,0x304e2d7e,0x388739fe,0x3a99394d,0x3bc93bdd,0x336531db,0x2f0e3593,0x3bf43b80,0x3b913baf,0x35343475,0xb5f1b04e,0x3b6e3bed,0x3b463b6e,0x36aa35f1,
0x3b413bd1,0x36c132d2,0x3bf73bfb,0x2de22c51,0x391d3a56,0x3a2738e2,0x3bec3bf2,0x30802f72,0x33f73748,0x3bc03b20,0x3bdb3be4,0x320d3147,0xb20d27da,0x3bdb3bff,0x3bc63bd1,0x339632d2,
0x311d31a6,0x30da3198,0x308b317d,0x30313154,0x2b9f2f99,0x297f2ebd,0x26a42dd1,0x20712cd6,0xacd6a071,0xadd1a6a4,0xaebda97f,0xaf99ab9f,0xb154b031,0xb17db08b,0xb198b0da,0xb1a6b11d,
0x297f3198,0xa071311d,0xab9f3031,0xaebd2dd1,0xb0dab08b,0xaf99b154,0xacd6b1a6,0xa6a4b17d,0x317d26a4,0x31a62cd6,0x31542f99,0x308b30da,0xadd12ebd,0xb0312b9f,0xb11d2071,0xb198a97f,
0xaebd317d,0xb11d3031,0xb1a62b9f,0xb0daa6a4,0x3198add1,0x3154a071,0x2f992cd6,0x297f308b,0xb08ba97f,0xacd6af99,0x2071b154,0x2dd1b198,0x26a430da,0xab9f31a6,0xb031311d,0xb17d2ebd,
0xb1a63154,0xb08b2dd1,0xa97fa6a4,0x2cd6b031,0xaf99311d,0xb198317d,0xb0da2ebd,0xab9fa071,0x20712b9f,0xaebd30da,0xb17d3198,0xb11d2f99,0x3031acd6,0x26a4297f,0xadd1308b,0xb15431a6,
0xaf99311d,0x26a4297f,0x30daaebd,0x3154b1a6,0x20712b9f,0x308badd1,0x317db198,0x2cd6b031,0x3031acd6,0x3198b17d,0x2dd1b08b,0xab9fa071,0x31a6b154,0x2ebdb0da,0xa97fa6a4,0xb11d2f99,
0x26a430da,0x3154a071,0x3031b11d,0xa97fb08b,0x2ebdb17d,0xacd6af99,0xb1a62b9f,0xadd13198,0xb1982dd1,0xab9f31a6,0x2f992cd6,0x317daebd,0x308b297f,0x311db031,0x2071b154,0xb0daa6a4,
0x30da308b,0x3031ab9f,0xacd6b1a6,0xb198a97f,0xb17da6a4,0xa071311d,0x31542f99,0x2ebdadd1,0x2dd1aebd,0xaf99b154,0xb11d2071,0x26a4317d,0x297f3198,0x31a62cd6,0x2b9fb031,0xb08bb0da,
0x31543031,0xa97faebd,0xb198b0da,0x20712cd6,0x311d31a6,0x2dd126a4,0xb08bb17d,0xaf99ab9f,0x2b9f2f99,0x317d308b,0xa6a4add1,0xb1a6b11d,0xacd6a071,0x30da3198,0x2ebd297f,0xb031b154,
0x2b9f2f99,0xb17db08b,0xa6a4add1,0x31a6311d,0xacd6a071,0xb0dab198,0x2ebd297f,0x30313154,0xb154b031,0xa97faebd,0x319830da,0x20712cd6,0xb11db1a6,0x2dd126a4,0x308b317d,0xaf99ab9f,
0xadd12ebd,0xaf99b154,0x311da071,0x26a4317d,0xa97fb198,0x31a62cd6,0xab9f3031,0xb08bb0da,0x30da308b,0xb0312b9f,0xacd6b1a6,0x3198297f,0xb17da6a4,0x2071b11d,0x31542f99,0xaebd2dd1,
0xb1982dd1,0x2b9fb1a6,0x2f992cd6,0xb17d2ebd,0x308b297f,0xb11d3031,0x2071b154,0x30da26a4,0xa6a4b0da,0x3154a071,0xb031311d,0xa97fb08b,0xaebd317d,0xacd6af99,0x31a6ab9f,0xadd13198,
0xb0312cd6,0x3198b17d,0xadd1308b,0xab9fa071,0xb1a63154,0x2ebdb0da,0x297f26a4,0xb11d2f99,0xaf99311d,0xa6a4a97f,0x30daaebd,0xb15431a6,0x20712b9f,0xb08b2dd1,0x317db198,0xacd63031,
0x20712b9f,0x2ebdb0da,0xb17d3198,0x311daf99,0x3031acd6,0xa6a4a97f,0xadd1308b,0x3154b1a6,0x31a6b154,0xb08b2dd1,0x297f26a4,0x2cd6b031,0x2f99b11d,0xb198317d,0x30daaebd,0xab9fa071,
0x308b297f,0xacd6af99,0xa0713154,0x2dd1b198,0xa6a4b0da,0xab9f31a6,0x3031b11d,0xb17d2ebd,0xaebd317d,0x311db031,0xb1a62b9f,0x30da26a4,0x3198add1,0xb1542071,0x2f992cd6,0xa97fb08b,
0x317d26a4,0xb1a6acd6,0x31542f99,0xb08bb0da,0xadd12ebd,0x3031ab9f,0xb11d2071,0x3198297f,0xa97fb198,0xa071311d,0x2b9fb031,0xaebd2dd1,0x30da308b,0xaf99b154,0x2cd631a6,0xa6a4b17d,
0x2cd62071,0xadd1a6a4,0x2ebd297f,0xaf99ab9f,0x31543031,0xb17db08b,0x319830da,0xb1a6b11d,0x311d31a6,0xb0dab198,0x308b317d,0xb031b154,0x2b9f2f99,0xa97faebd,0x26a42dd1,0xa071acd6,
0x2cd62071,0x2dd126a4,0x2ebd297f,0x2f992b9f,0x31543031,0x317d308b,0x319830da,0x31a6311d,0x311d31a6,0x30da3198,0x308b317d,0x30313154,0x2b9f2f99,0x297f2ebd,0x26a42dd1,0x20712cd6,
0x317d26a4,0x31a62cd6,0x31542f99,0x308b30da,0xadd12ebd,0xb0312b9f,0xb11d2071,0xb198a97f,0xa97fb198,0x2071b11d,0x2b9fb031,0x2ebdadd1,0x30da308b,0x2f993154,0x2cd631a6,0x26a4317d,
0x308b297f,0x2cd62f99,0xa0713154,0xadd13198,0xa6a4b0da,0x2b9fb1a6,0x3031b11d,0x317daebd,0xaebd317d,0xb11d3031,0xb1a62b9f,0xb0daa6a4,0x3198add1,0x3154a071,0x2f992cd6,0x297f308b,
0x20712b9f,0xaebd30da,0xb17d3198,0xb11d2f99,0x3031acd6,0x26a4297f,0xadd1308b,0xb15431a6,0x31a6b154,0x308badd1,0x297f26a4,0xacd63031,0x2f99b11d,0x3198b17d,0x30daaebd,0x2b9f2071,
0xb0312cd6,0xb198317d,0xadd1308b,0x2b9f2071,0xb1a63154,0xaebd30da,0x297f26a4,0x311daf99,0xaf99311d,0x26a4297f,0x30daaebd,0x3154b1a6,0x20712b9f,0x308badd1,0x317db198,0x2cd6b031,
0xb1982dd1,0xab9f31a6,0x2f992cd6,0x317daebd,0x308b297f,0x311db031,0x2071b154,0xb0daa6a4,0xa6a4b0da,0xb1542071,0xb031311d,0x297f308b,0xaebd317d,0x2cd62f99,0x31a6ab9f,0x2dd1b198,
0xadd12ebd,0x2f993154,0x311da071,0xa6a4b17d,0xa97fb198,0xb1a6acd6,0xab9f3031,0x308b30da,0x30da308b,0x3031ab9f,0xacd6b1a6,0xb198a97f,0xb17da6a4,0xa071311d,0x31542f99,0x2ebdadd1,
0x2b9f2f99,0x317d308b,0xa6a4add1,0xb1a6b11d,0xacd6a071,0x30da3198,0x2ebd297f,0xb031b154,0xb154b031,0x297f2ebd,0x319830da,0xa071acd6,0xb11db1a6,0xadd1a6a4,0x308b317d,0x2f992b9f,
0x31543031,0x297f2ebd,0xb198b0da,0xa071acd6,0x311d31a6,0xadd1a6a4,0xb08bb17d,0x2f992b9f,0x2b9f2f99,0xb17db08b,0xa6a4add1,0x31a6311d,0xacd6a071,0xb0dab198,0x2ebd297f,0x30313154,
0x30da308b,0xb0312b9f,0xacd6b1a6,0x3198297f,0xb17da6a4,0x2071b11d,0x31542f99,0xaebd2dd1,0x2dd1aebd,0x2f993154,0xb11d2071,0xa6a4b17d,0x297f3198,0xb1a6acd6,0x2b9fb031,0x308b30da,
0x26a430da,0xb1542071,0x3031b11d,0x297f308b,0x2ebdb17d,0x2cd62f99,0xb1a62b9f,0x2dd1b198,0xb1982dd1,0x2b9fb1a6,0x2f992cd6,0xb17d2ebd,0x308b297f,0xb11d3031,0x2071b154,0x30da26a4,
0xaf99311d,0xa6a4a97f,0x30daaebd,0xb15431a6,0x20712b9f,0xb08b2dd1,0x317db198,0xacd63031,0x3031acd6,0xb198317d,0x2dd1b08b,0x2b9f2071,0x31a6b154,0xaebd30da,0xa97fa6a4,0x311daf99,
0xb1a63154,0x308badd1,0xa97fa6a4,0xacd63031,0xaf99311d,0x3198b17d,0xb0da2ebd,0x2b9f2071,0x20712b9f,0x2ebdb0da,0xb17d3198,0x311daf99,0x3031acd6,0xa6a4a97f,0xadd1308b,0x3154b1a6,
0xaebd317d,0x311db031,0xb1a62b9f,0x30da26a4,0x3198add1,0xb1542071,0x2f992cd6,0xa97fb08b,0xb08ba97f,0x2cd62f99,0x2071b154,0xadd13198,0x26a430da,0x2b9fb1a6,0xb031311d,0x317daebd,
0x297f3198,0x2071b11d,0xab9f3031,0x2ebdadd1,0xb0dab08b,0x2f993154,0xacd6b1a6,0x26a4317d,0x317d26a4,0xb1a6acd6,0x31542f99,0xb08bb0da,0xadd12ebd,0x3031ab9f,0xb11d2071,0x3198297f,
0x311d31a6,0xb0dab198,0x308b317d,0xb031b154,0x2b9f2f99,0xa97faebd,0x26a42dd1,0xa071acd6,0xacd6a071,0x2dd126a4,0xaebda97f,0x2f992b9f,0xb154b031,0x317d308b,0xb198b0da,0x31a6311d,
0x313a31a8,0x30fd31a1,0x30b4318c,0x305f316a,0x2c543000,0x2a922f2d,0x286a2e49,0x24702d55,0xac540000,0xad55a470,0xae49a86a,0xaf2daa92,0xb13ab000,0xb16ab05f,0xb18cb0b4,0xb1a1b0fd,
0x2c5431a8,0x2470316a,0xa86a30b4,0xad552f2d,0xb13ab000,0xb05fb0fd,0xae49b18c,0xaa92b1a1,0x313a8000,0x31a12a92,0x318c2e49,0x30fd305f,0xac543000,0xaf2d2d55,0xb0b4286a,0xb16aa470,
0xac5431a8,0xb05f30fd,0xb18c2e49,0xb16a2470,0x313ab000,0x31a1aa92,0x30b4286a,0x2d552f2d,0xb13a0000,0xaf2dad55,0xa86ab0b4,0x2a92b1a1,0x2c543000,0xa470316a,0xae49318c,0xb0fd305f,
0xb13a31a8,0xb16a305f,0xae49286a,0x2470ad55,0xac543000,0xb0fd31a1,0xb18c30b4,0xaf2d2a92,0x2c548000,0xaa922f2d,0xb0b4318c,0xb1a130fd,0x313ab000,0x2d55a470,0xa86a2e49,0xb05f316a,
0xb13a31a8,0xaa922f2d,0x2e49a86a,0x31a1b0fd,0xac543000,0x2d55a470,0x318cb0b4,0x305fb16a,0x2c540000,0x316ab05f,0x30b4b18c,0x2470ad55,0x313ab000,0x30fdb1a1,0x286aae49,0xaf2d2a92,
0xac5431a8,0x2f2d2d55,0x318cae49,0x2a92b1a1,0x313ab000,0x2470b16a,0xb0b4a86a,0xb0fd305f,0xb13a8000,0xb05f30fd,0x286a30b4,0x316aa470,0x2c543000,0x31a1aa92,0x2e49b18c,0xad55af2d,
0x2c5431a8,0x31a12a92,0x286ab0b4,0xb0fdb05f,0xb13ab000,0xaf2d2d55,0x2e49318c,0x316a2470,0x313a8000,0xa470b16a,0xb18cae49,0xad552f2d,0xac543000,0x305f30fd,0x30b4a86a,0xaa92b1a1,
0x313a31a8,0x2d552470,0xb0b4b18c,0xaf2daa92,0x2c543000,0x316a305f,0xa86aae49,0xb1a1b0fd,0xac548000,0x30fd31a1,0x2e49286a,0xb05fb16a,0xb13ab000,0x2a922f2d,0x318c30b4,0xa470ad55,
0x313a31a8,0xad55a470,0xb0b4b18c,0x2f2d2a92,0x2c543000,0xb16ab05f,0xa86aae49,0x31a130fd,0xac548000,0xb0fdb1a1,0x2e49286a,0x305f316a,0xb13ab000,0xaa92af2d,0x318c30b4,0x24702d55,
0x2c5431a8,0xb1a1aa92,0x286ab0b4,0x30fd305f,0xb13ab000,0x2f2dad55,0x2e49318c,0xb16aa470,0x313a8000,0x2470316a,0xb18cae49,0x2d55af2d,0xac543000,0xb05fb0fd,0x30b4a86a,0x2a9231a1,
0xac5431a8,0xaf2dad55,0x318cae49,0xaa9231a1,0x313ab000,0xa470316a,0xb0b4a86a,0x30fdb05f,0xb13a8000,0x305fb0fd,0x286a30b4,0xb16a2470,0x2c543000,0xb1a12a92,0x2e49b18c,0x2d552f2d,
0xb13a31a8,0x2a92af2d,0x2e49a86a,0xb1a130fd,0xac543000,0xad552470,0x318cb0b4,0xb05f316a,0x2c548000,0xb16a305f,0x30b4b18c,0xa4702d55,0x313ab000,0xb0fd31a1,0x286aae49,0x2f2daa92,
0xb13a31a8,0x316ab05f,0xae49286a,0xa4702d55,0xac543000,0x30fdb1a1,0xb18c30b4,0x2f2daa92,0x2c548000,0x2a92af2d,0xb0b4318c,0x31a1b0fd,0x313ab000,0xad552470,0xa86a2e49,0x305fb16a,
0xac5431a8,0x305fb0fd,0xb18c2e49,0x316aa470,0x313ab000,0xb1a12a92,0x30b4286a,0xad55af2d,0xb13a8000,0x2f2d2d55,0xa86ab0b4,0xaa9231a1,0x2c543000,0x2470b16a,0xae49318c,0x30fdb05f,
0x2c5431a8,0xa470b16a,0xa86a30b4,0x2d55af2d,0xb13ab000,0x305f30fd,0xae49b18c,0x2a9231a1,0x313a8000,0xb1a1aa92,0x318c2e49,0xb0fdb05f,0xac543000,0x2f2dad55,0xb0b4286a,0x316a2470,
0x313a31a8,0xb0fdb1a1,0x30b4318c,0xb05fb16a,0x2c543000,0xaa92af2d,0x286a2e49,0xa470ad55,0xac548000,0x2d552470,0xae49a86a,0x2f2d2a92,0xb13ab000,0x316a305f,0xb18cb0b4,0x31a130fd,
0xac548000,0xad55a470,0xae49a86a,0xaf2daa92,0xb13ab000,0xb16ab05f,0xb18cb0b4,0xb1a1b0fd,0xb13ab1a8,0xb0fdb1a1,0xb0b4b18c,0xb05fb16a,0xac54b000,0xaa92af2d,0xa86aae49,0xa470ad55,
0xb13a8000,0xb1a1aa92,0xb18cae49,0xb0fdb05f,0x2c54b000,0x2f2dad55,0x30b4a86a,0x316a2470,0x2c5431a8,0x2470316a,0xa86a30b4,0xad552f2d,0xb13ab000,0xb05fb0fd,0xae49b18c,0xaa92b1a1,
0xb13a8000,0xaf2dad55,0xa86ab0b4,0x2a92b1a1,0x2c543000,0xa470316a,0xae49318c,0xb0fd305f,0x2c54b1a8,0x305fb0fd,0x318cae49,0x316aa470,0xb13a3000,0xb1a12a92,0xb0b4a86a,0xad55af2d,
0xac548000,0x2a92af2d,0x30b4b18c,0x31a1b0fd,0xb13a3000,0xad552470,0x286aae49,0x305fb16a,0xb13a31a8,0xb16a305f,0xae49286a,0x2470ad55,0xac543000,0xb0fd31a1,0xb18c30b4,0xaf2d2a92,
0x2c548000,0x316ab05f,0x30b4b18c,0x2470ad55,0x313ab000,0x30fdb1a1,0x286aae49,0xaf2d2a92,0x313ab1a8,0x2a92af2d,0xae49286a,0xb1a130fd,0x2c54b000,0xad552470,0xb18c30b4,0xb05f316a,
0x313a8000,0x305fb0fd,0xa86ab0b4,0xb16a2470,0xac54b000,0xb1a12a92,0xae49318c,0x2d552f2d,0xac5431a8,0x2f2d2d55,0x318cae49,0x2a92b1a1,0x313ab000,0x2470b16a,0xb0b4a86a,0xb0fd305f,
0x313a8000,0xa470b16a,0xb18cae49,0xad552f2d,0xac543000,0x305f30fd,0x30b4a86a,0xaa92b1a1,0xac54b1a8,0xb1a1aa92,0xa86a30b4,0x30fd305f,0x313a3000,0x2f2dad55,0xae49b18c,0xb16aa470,
0x2c548000,0xb0fdb1a1,0xae49a86a,0x305f316a,0x313a3000,0xaa92af2d,0xb18cb0b4,0x24702d55,0x313a31a8,0x2d552470,0xb0b4b18c,0xaf2daa92,0x2c543000,0x316a305f,0xa86aae49,0xb1a1b0fd,
0xac548000,0xb0fdb1a1,0x2e49286a,0x305f316a,0xb13ab000,0xaa92af2d,0x318c30b4,0x24702d55,0xb13ab1a8,0x2d552470,0x30b4318c,0xaf2daa92,0xac54b000,0x316a305f,0x286a2e49,0xb1a1b0fd,
0xb13a8000,0xa470b16a,0x318c2e49,0xad552f2d,0x2c54b000,0x305f30fd,0xb0b4286a,0xaa92b1a1,0x2c5431a8,0xb1a1aa92,0x286ab0b4,0x30fd305f,0xb13ab000,0x2f2dad55,0x2e49318c,0xb16aa470,
0xb13a8000,0x305fb0fd,0x286a30b4,0xb16a2470,0x2c543000,0xb1a12a92,0x2e49b18c,0x2d552f2d,0x2c54b1a8,0x2f2d2d55,0xb18c2e49,0x2a92b1a1,0xb13a3000,0x2470b16a,0x30b4286a,0xb0fd305f,
0xac548000,0x316ab05f,0xb0b4318c,0x2470ad55,0xb13a3000,0x30fdb1a1,0xa86a2e49,0xaf2d2a92,0xb13a31a8,0x2a92af2d,0x2e49a86a,0xb1a130fd,0xac543000,0xad552470,0x318cb0b4,0xb05f316a,
0x2c548000,0x2a92af2d,0xb0b4318c,0x31a1b0fd,0x313ab000,0xad552470,0xa86a2e49,0x305fb16a,0x313ab1a8,0xb16a305f,0x2e49a86a,0x2470ad55,0x2c54b000,0xb0fd31a1,0x318cb0b4,0xaf2d2a92,
0x313a8000,0xaf2dad55,0x286a30b4,0x2a92b1a1,0xac54b000,0xa470316a,0x2e49b18c,0xb0fd305f,0xac5431a8,0x305fb0fd,0xb18c2e49,0x316aa470,0x313ab000,0xb1a12a92,0x30b4286a,0xad55af2d,
0x313a8000,0xb1a1aa92,0x318c2e49,0xb0fdb05f,0xac543000,0x2f2dad55,0xb0b4286a,0x316a2470,0xac54b1a8,0x2470316a,0x286ab0b4,0xad552f2d,0x313a3000,0xb05fb0fd,0x2e49318c,0xaa92b1a1,
0x2c548000,0xad55a470,0x2e49286a,0xaf2daa92,0x313a3000,0xb16ab05f,0x318c30b4,0xb1a1b0fd,0x313a31a8,0xb0fdb1a1,0x30b4318c,0xb05fb16a,0x2c543000,0xaa92af2d,0x286a2e49,0xa470ad55,
0x319831a6,0x2ebd2f99,0xa6a4a071,0xb08bb031,0x3154317d,0x2cd62dd1,0xab9fa97f,0xb11db0da,0x30da311d,0x297f2b9f,0xadd1acd6,0xb17db154,0x3031308b,0x207126a4,0xaf99aebd,0xb1a6b198,
0x311d3198,0xb154b08b,0x2cd626a4,0x2b9f2ebd,0x2dd13031,0xb17db1a6,0x30da2f99,0xa97f2071,0xa071297f,0xaf99b0da,0x31a6317d,0xb031add1,0xaebdab9f,0xa6a4acd6,0x308b3154,0xb198b11d,
0x3031317d,0xa071add1,0xaf99a97f,0x31a630da,0xa6a42b9f,0x308b2cd6,0xb198b154,0x2ebd311d,0xb11daebd,0x31543198,0xacd6b08b,0xab9f26a4,0xb0dab1a6,0x297f2f99,0x2dd12071,0xb17db031,
0x2dd13154,0x317d311d,0x30da2b9f,0x297facd6,0xb031a6a4,0xa0712ebd,0x2f993198,0x31a6308b,0xb08bb1a6,0xb198af99,0xaebd2071,0x26a43031,0x2cd6a97f,0xab9fb0da,0xb11db17d,0xb154add1,
0x297f311d,0xadd12b9f,0xb17dacd6,0xb0dab154,0xb1a6aebd,0xb031b198,0xa071b08b,0x2f99a6a4,0x26a4af99,0x308b2071,0x31983031,0x2ebd31a6,0x315430da,0x2cd6317d,0xab9f2dd1,0xb11da97f,
0xa07130da,0xaf99b17d,0x31a62dd1,0xb031297f,0xb08bb11d,0x31982b9f,0xaebd2cd6,0xa6a4b154,0x315426a4,0xacd62ebd,0xab9fb198,0x311d308b,0xa97f3031,0xadd1b1a6,0x317d2f99,0xb0da2071,
0xab9f308b,0x311da6a4,0xb154aebd,0x2cd63198,0xa97fb1a6,0xadd12f99,0x317d2071,0xb0dab031,0x303130da,0xa071b17d,0xaf992dd1,0x31a6297f,0xb198acd6,0x2ebd3154,0x26a4b11d,0xb08b2b9f,
0xaebd3031,0x26a431a6,0x308b2f99,0x3198a071,0x2cd6b0da,0xab9fb17d,0xb11dadd1,0xb154297f,0xa97f3154,0x2dd1311d,0x317d2b9f,0x30daacd6,0x2071b198,0xaf99b08b,0xb1a6a6a4,0xb0312ebd,
0xb08b2f99,0xb198a071,0xaebdb031,0x26a4b1a6,0x311dadd1,0x3154297f,0x2cd630da,0xab9f317d,0xb17d2b9f,0xb0daacd6,0xa97fb154,0x2dd1b11d,0x31a6a6a4,0x30312ebd,0x20713198,0xaf99308b,
0xb1542ebd,0x2cd6b198,0x2b9f308b,0xb11da6a4,0x317da071,0xb0da3031,0x297fb1a6,0x2dd12f99,0xaf99add1,0x31a6a97f,0xb03130da,0x2071b17d,0x26a4311d,0xb08bab9f,0x3198acd6,0xaebd3154,
0xb1a62dd1,0x3031297f,0xa071b0da,0xaf99317d,0x2ebd2cd6,0x26a4b154,0xb08b311d,0x3198ab9f,0x2b9fb198,0xb11d308b,0x3154a6a4,0xacd6aebd,0xb17d2f99,0x30da2071,0xa97fb031,0xadd131a6,
0xb17d2cd6,0xb0da3154,0xa97f311d,0x2dd12b9f,0xa071308b,0x2f9926a4,0x31a6aebd,0x3031b198,0x3198b031,0x2ebdb1a6,0xa6a4af99,0xb08b2071,0xab9fadd1,0xb11d297f,0xb15430da,0xacd6317d,
0xb0da2b9f,0xa97facd6,0x2dd1b154,0x317db11d,0xaf993198,0xb1a6308b,0xb03126a4,0xa071aebd,0x2ebd2071,0xa6a43031,0xb08b31a6,0xb1982f99,0x311db17d,0x3154add1,0x2cd6297f,0xab9f30da,
0xaf99297f,0x31a6b0da,0xb031317d,0x2071add1,0xb1983154,0x2ebdb11d,0x26a42b9f,0xb08b2cd6,0xacd6308b,0xab9fa6a4,0x311daebd,0xb1543198,0x2dd1a071,0xb17d3031,0x30dab1a6,0xa97f2f99,
0xacd626a4,0xab9f2ebd,0x311db198,0xb154308b,0xb0da2f99,0x297f2071,0x2dd1b031,0xb17d31a6,0xb1a6317d,0x3031add1,0xa071a97f,0xaf9930da,0xb08b3154,0x3198b11d,0xaebd2b9f,0xa6a42cd6,
0xa6a42071,0xb08b3031,0xb19831a6,0xaebd2f99,0xab9f297f,0xb11d30da,0xb154317d,0xacd62dd1,0xadd12cd6,0xb17d3154,0xb0da311d,0xa97f2b9f,0xaf992ebd,0xb1a63198,0xb031308b,0xa07126a4,
0x26a42071,0x308b3031,0x319831a6,0x2ebd2f99,0x2b9f297f,0x311d30da,0x3154317d,0x2cd62dd1,0x2dd12cd6,0x317d3154,0x30da311d,0x297f2b9f,0x2f992ebd,0x31a63198,0x3031308b,0x207126a4,
0x2cd626a4,0x2b9f2ebd,0xb11db198,0x3154308b,0x30da2f99,0xa97f2071,0xadd1b031,0x317d31a6,0x31a6317d,0xb031add1,0x2071a97f,0x2f9930da,0x308b3154,0xb198b11d,0x2ebd2b9f,0x26a42cd6,
0x2f99297f,0xb1a6b0da,0x3031317d,0xa071add1,0x31983154,0xaebdb11d,0xa6a42b9f,0x308b2cd6,0x2cd6308b,0x2b9fa6a4,0xb11daebd,0x31543198,0xadd1a071,0x317d3031,0xb0dab1a6,0x297f2f99,
0x30da2b9f,0x297facd6,0xadd1b154,0xb17db11d,0x2f993198,0x31a6308b,0x303126a4,0x2071aebd,0xaebd2071,0x26a43031,0x308b31a6,0x31982f99,0xb11db17d,0xb154add1,0xacd6297f,0x2b9f30da,
0x317d2cd6,0x30da3154,0x297f311d,0xadd12b9f,0x2071308b,0xaf9926a4,0xb1a6aebd,0xb031b198,0xb198b031,0xaebdb1a6,0x26a4af99,0x308b2071,0x2b9fadd1,0x311d297f,0x315430da,0x2cd6317d,
0x31a62dd1,0xb031297f,0x2071b0da,0x2f99317d,0xaebd2cd6,0xa6a4b154,0x308b311d,0xb198ab9f,0xab9fb198,0x311d308b,0xb154a6a4,0x2cd6aebd,0x317d2f99,0xb0da2071,0x297fb031,0x2dd131a6,
0x31542ebd,0xacd6b198,0xab9f308b,0x311da6a4,0xb17da071,0x30da3031,0xa97fb1a6,0xadd12f99,0x2f99add1,0xb1a6a97f,0x303130da,0xa071b17d,0xa6a4311d,0x308bab9f,0xb198acd6,0x2ebd3154,
0x308b2f99,0x3198a071,0x2ebdb031,0xa6a4b1a6,0xb11dadd1,0xb154297f,0xacd630da,0x2b9f317d,0x317d2b9f,0x30daacd6,0x297fb154,0xadd1b11d,0xb1a6a6a4,0xb0312ebd,0xa0713198,0x2f99308b,
0x2ebd3031,0xa6a431a6,0xb08b2f99,0xb198a071,0xacd6b0da,0x2b9fb17d,0x311dadd1,0x3154297f,0x297f3154,0xadd1311d,0xb17d2b9f,0xb0daacd6,0xa071b198,0x2f99b08b,0x31a6a6a4,0x30312ebd,
0x2b9f308b,0xb11da6a4,0x3154aebd,0xacd63198,0x297fb1a6,0x2dd12f99,0xb17d2071,0x30dab031,0xb03130da,0x2071b17d,0x2f992dd1,0xb1a6297f,0x3198acd6,0xaebd3154,0xa6a4b11d,0x308b2b9f,
0x207130da,0x2f99b17d,0xb1a62dd1,0x3031297f,0x308bb11d,0xb1982b9f,0x2ebd2cd6,0x26a4b154,0xb15426a4,0x2cd62ebd,0x2b9fb198,0xb11d308b,0x297f3031,0x2dd1b1a6,0xb17d2f99,0x30da2071,
0xa97f311d,0x2dd12b9f,0x317dacd6,0x30dab154,0x31a6aebd,0x3031b198,0x2071b08b,0xaf99a6a4,0xa6a4af99,0xb08b2071,0xb1983031,0xaebd31a6,0xb15430da,0xacd6317d,0x2b9f2dd1,0x311da97f,
0xadd13154,0xb17d311d,0xb0da2b9f,0xa97facd6,0x3031a6a4,0x20712ebd,0xaf993198,0xb1a6308b,0x308bb1a6,0x3198af99,0x2ebd2071,0xa6a43031,0xacd6a97f,0x2b9fb0da,0x311db17d,0x3154add1,
0xb031317d,0x2071add1,0x2f99a97f,0xb1a630da,0x26a42b9f,0xb08b2cd6,0x3198b154,0xaebd311d,0x311daebd,0xb1543198,0x2cd6b08b,0x2b9f26a4,0x30dab1a6,0xa97f2f99,0xadd12071,0x317db031,
0xb11d3198,0x3154b08b,0xacd626a4,0xab9f2ebd,0xadd13031,0x317db1a6,0xb0da2f99,0x297f2071,0x2071297f,0x2f99b0da,0xb1a6317d,0x3031add1,0x2ebdab9f,0x26a4acd6,0xb08b3154,0x3198b11d,
0xb19831a6,0xaebd2f99,0x26a4a071,0x308bb031,0xb154317d,0xacd62dd1,0x2b9fa97f,0x311db0da,0xb0da311d,0xa97f2b9f,0x2dd1acd6,0x317db154,0xb031308b,0xa07126a4,0x2f99aebd,0x31a6b198,
0x319831a6,0xb08b2f99,0x2ebd2f99,0xb198a071,0x3154317d,0x311dadd1,0x2cd62dd1,0x3154297f,0x30da311d,0xb17d2b9f,0x297f2b9f,0xb0daacd6,0x3031308b,0x31a6a6a4,0x207126a4,0x30312ebd,
0x311d3198,0xb1542ebd,0xb154b08b,0x2cd6b198,0x2dd13031,0x317da071,0xb17db1a6,0xb0da3031,0xa071297f,0xaf99add1,0xaf99b0da,0x31a6a97f,0xaebdab9f,0x26a4311d,0xa6a4acd6,0xb08bab9f,
0x3031317d,0xb1a62dd1,0xa071add1,0x3031297f,0xa6a42b9f,0x2ebd2cd6,0x308b2cd6,0x26a4b154,0xb11daebd,0x2b9fb198,0x31543198,0xb11d308b,0xb0dab1a6,0xb17d2f99,0x297f2f99,0x30da2071,
0x2dd13154,0xb17d2cd6,0x317d311d,0xb0da3154,0xb031a6a4,0xa071308b,0xa0712ebd,0x2f9926a4,0xb08bb1a6,0x3198b031,0xb198af99,0x2ebdb1a6,0x2cd6a97f,0xab9fadd1,0xab9fb0da,0xb11d297f,
0x297f311d,0xb0da2b9f,0xadd12b9f,0xa97facd6,0xb1a6aebd,0xaf993198,0xb031b198,0xb1a6308b,0x26a4af99,0x2ebd2071,0x308b2071,0xa6a43031,0x315430da,0x311db17d,0x2cd6317d,0x3154add1,
0xa07130da,0xaf99297f,0xaf99b17d,0x31a6b0da,0xb08bb11d,0xb1983154,0x31982b9f,0x2ebdb11d,0x315426a4,0xacd6308b,0xacd62ebd,0xab9fa6a4,0xa97f3031,0x2dd1a071,0xadd1b1a6,0xb17d3031,
0xab9f308b,0xacd626a4,0x311da6a4,0xab9f2ebd,0xa97fb1a6,0xb0da2f99,0xadd12f99,0x297f2071,0x303130da,0xb1a6317d,0xa071b17d,0x3031add1,0xb198acd6,0xb08b3154,0x2ebd3154,0x3198b11d,
0xaebd3031,0xa6a42071,0x26a431a6,0xb08b3031,0x2cd6b0da,0xab9f297f,0xab9fb17d,0xb11d30da,0xa97f3154,0xadd12cd6,0x2dd1311d,0xb17d3154,0x2071b198,0xaf992ebd,0xaf99b08b,0xb1a63198,
0x319831a6,0xb08b2f99,0x2ebd2f99,0xb198a071,0x3154317d,0x311dadd1,0x2cd62dd1,0x3154297f,0x30da311d,0xb17d2b9f,0x297f2b9f,0xb0daacd6,0x3031308b,0x31a6a6a4,0x207126a4,0x30312ebd,
0x311d3198,0xb1542ebd,0xb154b08b,0x2cd6b198,0x2dd13031,0x317da071,0xb17db1a6,0xb0da3031,0xa071297f,0xaf99add1,0xaf99b0da,0x31a6a97f,0xaebdab9f,0x26a4311d,0xa6a4acd6,0xb08bab9f,
0x3031317d,0xb1a62dd1,0xa071add1,0x3031297f,0xa6a42b9f,0x2ebd2cd6,0x308b2cd6,0x26a4b154,0xb11daebd,0x2b9fb198,0x31543198,0xb11d308b,0xb0dab1a6,0xb17d2f99,0x297f2f99,0x30da2071,
0x2dd13154,0xb17d2cd6,0x317d311d,0xb0da3154,0xb031a6a4,0xa071308b,0xa0712ebd,0x2f9926a4,0xb08bb1a6,0x3198b031,0xb198af99,0x2ebdb1a6,0x2cd6a97f,0xab9fadd1,0xab9fb0da,0xb11d297f,
0x297f311d,0xb0da2b9f,0xadd12b9f,0xa97facd6,0xb1a6aebd,0xaf993198,0xb031b198,0xb1a6308b,0x26a4af99,0x2ebd2071,0x308b2071,0xa6a43031,0x315430da,0x311db17d,0x2cd6317d,0x3154add1,
0xa07130da,0xaf99297f,0xaf99b17d,0x31a6b0da,0xb08bb11d,0xb1983154,0x31982b9f,0x2ebdb11d,0x315426a4,0xacd6308b,0xacd62ebd,0xab9fa6a4,0xa97f3031,0x2dd1a071,0xadd1b1a6,0xb17d3031,
0xab9f308b,0xacd626a4,0x311da6a4,0xab9f2ebd,0xa97fb1a6,0xb0da2f99,0xadd12f99,0x297f2071,0x303130da,0xb1a6317d,0xa071b17d,0x3031add1,0xb198acd6,0xb08b3154,0x2ebd3154,0x3198b11d,
0xaebd3031,0xa6a42071,0x26a431a6,0xb08b3031,0x2cd6b0da,0xab9f297f,0xab9fb17d,0xb11d30da,0xa97f3154,0xadd12cd6,0x2dd1311d,0xb17d3154,0x2071b198,0xaf992ebd,0xaf99b08b,0xb1a63198,
0x26a42071,0x2ebd3031,0x308b3031,0xa6a431a6,0x2b9f297f,0xacd6b0da,0x311d30da,0x2b9fb17d,0x2dd12cd6,0x297f3154,0x317d3154,0xadd1311d,0x2f992ebd,0xa071b198,0x31a63198,0x2f99b08b,
0x2cd626a4,0x2b9f308b,0x2b9f2ebd,0xb11da6a4,0x30da2f99,0x297fb1a6,0xa97f2071,0x2dd12f99,0x31a6317d,0xb03130da,0xb031add1,0x2071b17d,0x308b3154,0x3198acd6,0xb198b11d,0xaebd3154,
0x2f99297f,0x207130da,0xb1a6b0da,0x2f99b17d,0x31983154,0x308bb11d,0xaebdb11d,0xb1982b9f,0x2cd6308b,0xb15426a4,0x2b9fa6a4,0x2cd62ebd,0xadd1a071,0x297f3031,0x317d3031,0x2dd1b1a6,
0x30da2b9f,0xa97f311d,0x297facd6,0x2dd12b9f,0x2f993198,0x31a6aebd,0x31a6308b,0x3031b198,0xaebd2071,0xa6a4af99,0x26a43031,0xb08b2071,0xb11db17d,0xb15430da,0xb154add1,0xacd6317d,
0x317d2cd6,0xadd13154,0x30da3154,0xb17d311d,0x2071308b,0x3031a6a4,0xaf9926a4,0x20712ebd,0xb198b031,0x308bb1a6,0xaebdb1a6,0x3198af99,0x2b9fadd1,0xacd6a97f,0x311d297f,0x2b9fb0da,
0x31a62dd1,0xb031317d,0xb031297f,0x2071add1,0xaebd2cd6,0x26a42b9f,0xa6a4b154,0xb08b2cd6,0xab9fb198,0x311daebd,0x311d308b,0xb1543198,0x317d2f99,0x30dab1a6,0xb0da2071,0xa97f2f99,
0x31542ebd,0xb11d3198,0xacd6b198,0x3154b08b,0xb17da071,0xadd13031,0x30da3031,0x317db1a6,0x2f99add1,0x2071297f,0xb1a6a97f,0x2f99b0da,0xa6a4311d,0x2ebdab9f,0x308bab9f,0x26a4acd6,
0x308b2f99,0xb19831a6,0x3198a071,0xaebd2f99,0xb11dadd1,0xb154317d,0xb154297f,0xacd62dd1,0x317d2b9f,0xb0da311d,0x30daacd6,0xa97f2b9f,0xb1a6a6a4,0xb031308b,0xb0312ebd,0xa07126a4,
0xa6a4a071,0xaebdb031,0xb08bb031,0x26a4b1a6,0xab9fa97f,0x2cd630da,0xb11db0da,0xab9f317d,0xadd1acd6,0xa97fb154,0xb17db154,0x2dd1b11d,0xaf99aebd,0x20713198,0xb1a6b198,0xaf99308b,
0xacd6a6a4,0xab9fb08b,0xab9faebd,0x311d26a4,0xb0daaf99,0xa97f31a6,0x297fa071,0xadd1af99,0xb1a6b17d,0x3031b0da,0x30312dd1,0xa071317d,0xb08bb154,0xb1982cd6,0x3198311d,0x2ebdb154,
0xaf99a97f,0xa071b0da,0x31a630da,0xaf99317d,0xb198b154,0xb08b311d,0x2ebd311d,0x3198ab9f,0xacd6b08b,0x3154a6a4,0xab9f26a4,0xacd6aebd,0x2dd12071,0xa97fb031,0xb17db031,0xadd131a6,
0xb0daab9f,0x297fb11d,0xa97f2cd6,0xadd1ab9f,0xaf99b198,0xb1a62ebd,0xb1a6b08b,0xb0313198,0x2ebda071,0x26a42f99,0xa6a4b031,0x308ba071,0x311d317d,0x3154b0da,0x31542dd1,0x2cd6b17d,
0xb17dacd6,0x2dd1b154,0xb0dab154,0x317db11d,0xa071b08b,0xb03126a4,0x2f99a6a4,0xa071aebd,0x31983031,0xb08b31a6,0x2ebd31a6,0xb1982f99,0xab9f2dd1,0x2cd6297f,0xb11da97f,0xab9f30da,
0xb1a6add1,0x3031b17d,0x3031a97f,0xa0712dd1,0x2ebdacd6,0xa6a4ab9f,0x26a43154,0x308bacd6,0x2b9f3198,0xb11d2ebd,0xb11db08b,0x3154b198,0xb17daf99,0xb0da31a6,0x30daa071,0x297faf99,
0xb154aebd,0x311db198,0x2cd63198,0xb154308b,0x317d2071,0x2dd1b031,0xb0dab031,0xb17d31a6,0xaf992dd1,0xa071a97f,0x31a6297f,0xaf9930da,0x26a4b11d,0xaebd2b9f,0xb08b2b9f,0xa6a42cd6,
0xb08baf99,0x3198b1a6,0xb1982071,0x2ebdaf99,0x311d2dd1,0x3154b17d,0x3154a97f,0x2cd6add1,0xb17dab9f,0x30dab11d,0xb0da2cd6,0x297fab9f,0x31a626a4,0x3031b08b,0x3031aebd,0x2071a6a4,
0x31a831a8,0x31a8,0x31a831a8,0x8000b1a8,0x31a831a8,0x31a8,0x31a831a8,0x8000b1a8,0x31a831a8,0x31a8,0x31a831a8,0x8000b1a8,0x31a831a8,0x800031a8,0x31a831a8,0x8000b1a8,
0x318c31a8,0xa86a31a8,0x30b4313a,0x2e49b13a,0x2e493000,0xb0b43000,0x286a2c54,0x318cac54,0xa86a0000,0xb18c0000,0xae49ac54,0x30b42c54,0xb0b4b000,0xae49b000,0xb18cb13a,0x286a313a,
0x313a31a8,0xac5431a8,0x2c543000,0x313ab000,0xac540000,0xb13a0000,0xb13ab000,0x2c543000,0xb13ab1a8,0x2c54b1a8,0xac54b000,0xb13a3000,0x2c548000,0x313a8000,0x313a3000,0xac54b000,
0x30b431a8,0xae4931a8,0xa86a2c54,0x318cac54,0xb18cb000,0xa86ab000,0xae49b13a,0xb0b4313a,0x2e498000,0x30b48000,0x318c313a,0x286ab13a,0x286a3000,0xb18c3000,0xb0b4ac54,0x2e492c54,
0x300031a8,0xb00031a8,0xb0000000,0x30008000,0xb000b1a8,0x3000b1a8,0x30008000,0xb0000000,0x300031a8,0xb00031a8,0xb0000000,0x30008000,0xb000b1a8,0x3000b1a8,0x30008000,0xb0008000,
0x2e4931a8,0xb0b431a8,0xb18cac54,0x286a2c54,0x286ab000,0x318cb000,0x30b4313a,0x2e49b13a,0xb0b40000,0xae498000,0xa86ab13a,0xb18c313a,0x318c3000,0xa86a3000,0xae492c54,0x30b4ac54,
0x2c5431a8,0xb13a31a8,0xb13ab000,0xac543000,0x313a8000,0x2c548000,0xac543000,0x313ab000,0xac54b1a8,0x313ab1a8,0x313a3000,0x2c54b000,0xb13a0000,0xac548000,0x2c54b000,0xb13a3000,
0x286a31a8,0xb18c31a8,0xae49b13a,0xb0b4313a,0x30b43000,0xae493000,0xb18cac54,0xa86a2c54,0x318c8000,0x286a8000,0xb0b42c54,0x2e49ac54,0x2e49b000,0x30b4b000,0xa86a313a,0x318cb13a,
0x31a831a8,0x800031a8,0x31a831a8,0x8000b1a8,0x31a831a8,0x800031a8,0x31a831a8,0x8000b1a8,0x31a831a8,0x800031a8,0x31a831a8,0x8000b1a8,0x31a831a8,0x800031a8,0x31a831a8,0x8000b1a8,
0xb18cb1a8,0x286ab1a8,0xb0b4b13a,0xae49313a,0xae49b000,0x30b4b000,0xa86aac54,0xb18c2c54,0x286a8000,0x318c8000,0x2e492c54,0xb0b4ac54,0x30b43000,0x2e493000,0x318c313a,0xa86ab13a,
0x313a31a8,0xac5431a8,0x2c543000,0x313ab000,0xac540000,0xb13a8000,0xb13ab000,0x2c543000,0xb13ab1a8,0x2c54b1a8,0xac54b000,0xb13a3000,0x2c548000,0x313a8000,0x313a3000,0xac54b000,
0xb0b4b1a8,0x2e49b1a8,0x286aac54,0xb18c2c54,0x318c3000,0x286a3000,0x2e49313a,0x30b4b13a,0xae490000,0xb0b40000,0xb18cb13a,0xa86a313a,0xa86ab000,0x318cb000,0x30b42c54,0xae49ac54,
0x300031a8,0xb00031a8,0xb0000000,0x30008000,0xb000b1a8,0x3000b1a8,0x30008000,0xb0000000,0x300031a8,0xb00031a8,0xb0008000,0x30008000,0xb000b1a8,0x3000b1a8,0x30008000,0xb0000000,
0xae49b1a8,0x30b4b1a8,0x318c2c54,0xa86aac54,0xa86a3000,0xb18c3000,0xb0b4b13a,0xae49313a,0x30b48000,0x2e498000,0x286a313a,0x318cb13a,0xb18cb000,0x286ab000,0x2e49ac54,0xb0b42c54,
0x2c5431a8,0xb13a31a8,0xb13ab000,0xac543000,0x313a8000,0x2c548000,0xac543000,0x313ab000,0xac54b1a8,0x313ab1a8,0x313a3000,0x2c54b000,0xb13a8000,0xac540000,0x2c54b000,0xb13a3000,
0xa86ab1a8,0x318cb1a8,0x2e49313a,0x30b4b13a,0xb0b4b000,0x2e49b000,0x318c2c54,0x286aac54,0xb18c8000,0xa86a0000,0x30b4ac54,0xae492c54,0xae493000,0xb0b43000,0x286ab13a,0xb18c313a,
0xb1a831a8,0x31a80000,0xb1a831a8,0xb1a80000,0xb1a831a8,0x31a88000,0xb1a831a8,0xb1a80000,0xb1a831a8,0x31a88000,0xb1a831a8,0xb1a80000,0xb1a831a8,0x31a88000,0xb1a831a8,0xb1a80000,
0x286a0000,0x318c0000,0x2e492c54,0xb0b4ac54,0x30b43000,0x2e493000,0x318c313a,0xa86ab13a,0x318c31a8,0xa86a31a8,0x30b4313a,0x2e49b13a,0x2e493000,0xb0b43000,0x286a2c54,0x318cac54,
0x2c540000,0x313a0000,0x313a3000,0xac54b000,0x313a31a8,0xac5431a8,0x2c543000,0x313ab000,0xac540000,0xb13a0000,0xb13ab000,0x2c543000,0xb13ab1a8,0x2c54b1a8,0xac54b000,0xb13a3000,
0x2e490000,0x30b40000,0x318c313a,0x286ab13a,0x286a3000,0xb18c3000,0xb0b4ac54,0x2e492c54,0xb0b4b1a8,0x2e49b1a8,0x286aac54,0xb18c2c54,0x318c3000,0x286a3000,0x2e49313a,0x30b4b13a,
0x30000000,0x30000000,0x300031a8,0x3000b1a8,0xb0000000,0xb0000000,0xb000b1a8,0xb00031a8,0x30008000,0x30008000,0x300031a8,0x3000b1a8,0xb0000000,0xb0000000,0xb000b1a8,0xb00031a8,
0x30b40000,0x2e490000,0x286a313a,0x318cb13a,0xb18cb000,0x286ab000,0x2e49ac54,0xb0b42c54,0x2e4931a8,0xb0b431a8,0xb18cac54,0x286a2c54,0x286ab000,0x318cb000,0x30b4313a,0x2e49b13a,
0x313a0000,0x2c540000,0xac543000,0x313ab000,0xac54b1a8,0x313ab1a8,0x313a3000,0x2c54b000,0xb13a0000,0xac540000,0x2c54b000,0xb13a3000,0x2c5431a8,0xb13a31a8,0xb13ab000,0xac543000,
0x318c0000,0x286a0000,0xb0b42c54,0x2e49ac54,0x2e49b000,0x30b4b000,0xa86a313a,0x318cb13a,0xa86ab1a8,0x318cb1a8,0x2e49313a,0x30b4b13a,0xb0b4b000,0x2e49b000,0x318c2c54,0x286aac54,
0xb1a831a8,0x31a88000,0xb1a831a8,0xb1a80000,0xb1a831a8,0x31a88000,0xb1a831a8,0xb1a80000,0xb1a831a8,0x31a88000,0xb1a831a8,0xb1a88000,0xb1a831a8,0x31a88000,0xb1a831a8,0xb1a80000,
0xa86a0000,0xb18c0000,0xae49ac54,0x30b42c54,0xb0b4b000,0xae49b000,0xb18cb13a,0x286a313a,0xb18cb1a8,0x286ab1a8,0xb0b4b13a,0xae49313a,0xae49b000,0x30b4b000,0xa86aac54,0xb18c2c54,
0x2c548000,0x313a8000,0x313a3000,0xac54b000,0x313a31a8,0xac5431a8,0x2c543000,0x313ab000,0xac540000,0xb13a0000,0xb13ab000,0x2c543000,0xb13ab1a8,0x2c54b1a8,0xac54b000,0xb13a3000,
0xae490000,0xb0b40000,0xb18cb13a,0xa86a313a,0xa86ab000,0x318cb000,0x30b42c54,0xae49ac54,0x30b431a8,0xae4931a8,0xa86a2c54,0x318cac54,0xb18cb000,0xa86ab000,0xae49b13a,0xb0b4313a,
0x30008000,0x30008000,0x300031a8,0x3000b1a8,0xb0000000,0xb0000000,0xb000b1a8,0xb00031a8,0x30008000,0x30008000,0x300031a8,0x3000b1a8,0xb0000000,0xb0008000,0xb000b1a8,0xb00031a8,
0xb0b40000,0xae498000,0xa86ab13a,0xb18c313a,0x318c3000,0xa86a3000,0xae492c54,0x30b4ac54,0xae49b1a8,0x30b4b1a8,0x318c2c54,0xa86aac54,0xa86a3000,0xb18c3000,0xb0b4b13a,0xae49313a,
0x313a8000,0x2c548000,0xac543000,0x313ab000,0xac54b1a8,0x313ab1a8,0x313a3000,0x2c54b000,0xb13a0000,0xac548000,0x2c54b000,0xb13a3000,0x2c5431a8,0xb13a31a8,0xb13ab000,0xac543000,
0xb18c0000,0xa86a0000,0x30b4ac54,0xae492c54,0xae493000,0xb0b43000,0x286ab13a,0xb18c313a,0x286a31a8,0xb18c31a8,0xae49b13a,0xb0b4313a,0x30b43000,0xae493000,0xb18cac54,0xa86a2c54,
0x3bea3bfe,0x30b22a48,0x3bf63bfe,0x2e462a48,0x3b883bc3,0x356433c6,0x3bd93bea,0x323e30b2,0x3add3b3b,0x381d36d7,0x3ba83bc3,0x34a533c6,0x39ed3a6d,0x395f38c4,0x3b643b88,0x361f3564,
0x3bec3bfe,0x30802a48,0x3bf73bfe,0x2de22a48,0x3b953bc9,0x351d3365,0x3be03bed,0x31aa304e,0x3afc3b50,0x37cd367c,0x3bb93bce,0x342c3303,0x3a273a99,0x391d3887,0x3b843ba0,0x357c34d5,
0x3bed3bfe,0x304e2a48,0x3bf83bfe,0x2d7e2a48,0x3ba03bce,0x34d53303,0x3be63bf1,0x31152fd6,0x3b1a3b64,0x375e361f,0x3bc93bd9,0x3365323e,0x3a5e3ac2,0x38d83848,0x3ba03bb6,0x34d53444,
0x3bef3bfe,0x301d2a48,0x3bf93bfe,0x2d1a2a48,0x3bab3bd4,0x348d32a1,0x3bec3bf4,0x30802f0e,0x3b363b77,0x36ee35c2,0x3bd63be2,0x326f3179,0x3a923ae9,0x38913807,0x3bb93bc9,0x342c3365,
0x3bf13bfe,0x2fd62a48,0x3bfa3bfe,0x2cb52a48,0x3bb63bd9,0x3444323e,0x3bf13bf6,0x2fd62e46,0x3b503b88,0x367c3564,0x3be23bea,0x317930b2,0x3ac23b0e,0x3848378b,0x3bce3bd9,0x3303323e,
0x3bf23bfe,0x2f722a48,0x3bfb3bfe,0x2c512a48,0x3bc03bdd,0x33f731db,0x3bf53bf8,0x2eaa2d7e,0x3b693b99,0x36083505,0x3bec3bf1,0x30802fd6,0x3af03b30,0x37f93705,0x3be03be6,0x31aa3115,
0x3bf43bfe,0x2f0e2a48,0x3bfc3bfe,0x2bd92a48,0x3bc93be2,0x33653179,0x3bf83bfa,0x2d7e2cb5,0x3b803ba8,0x359334a5,0x3bf43bf6,0x2f0e2e46,0x3b1a3b50,0x375e367c,0x3bed3bf1,0x304e2fd6,
0x3bf53bfe,0x2eaa2a48,0x3bfd3bfe,0x2b112a48,0x3bd13be6,0x32d23115,0x3bfb3bfc,0x2c512bd9,0x3b953bb6,0x351d3444,0x3bf93bfa,0x2d1a2cb5,0x3b413b6e,0x36c135f1,0x3bf73bf8,0x2de22d7e,
0x38c4395f,0x3a6d39ed,0x3b0e3b3b,0x378b36d7,0x36d7381d,0x3b3b3add,0x3aa73add,0x3872381d,0x33c63564,0x3bc33b88,0x3a2f3a6d,0x391338c4,0x2a4830b2,0x3bfe3bea,0x39a839ed,0x39a8395f,
0x391d39a8,0x3a2739a8,0x3b413b64,0x36c1361f,0x37cd3887,0x3afc3a99,0x3af03b1a,0x37f9375e,0x351d367c,0x3b953b50,0x3a923ac2,0x38913848,0x30803365,0x3bec3bc9,0x3a273a5e,0x391d38d8,
0x397239ed,0x39dc395f,0x3b6e3b88,0x35f13564,0x385d38ec,0x3ab53a4f,0x3b303b50,0x3705367c,0x364e378b,0x3b5a3b0e,0x3ae93b0e,0x3807378b,0x33653505,0x3bc93b99,0x3a993ac2,0x38873848,
0x39c33a2f,0x398d3913,0x3b953ba8,0x351d34a5,0x38ce394d,0x3a6539fe,0x3b693b80,0x36083593,0x37753848,0x3b143ac2,0x3b363b50,0x36ee367c,0x351d364e,0x3b953b5a,0x3afc3b1a,0x37cd375e,
0x3a0f3a6d,0x393a38c4,0x3bb63bc3,0x344433c6,0x393a39a8,0x3a0f39a8,0x3b993ba8,0x350534a5,0x384838c4,0x3ac23a6d,0x3b773b88,0x35c23564,0x367c378b,0x3b503b0e,0x3b503b64,0x367c361f,
0x3a563aa7,0x38e23872,0x3bd13bd9,0x32d2323e,0x399f39fe,0x39b1394d,0x3bc03bc9,0x33f73365,0x38ce393a,0x3a653a0f,0x3bab3bb6,0x348d3444,0x37cd385d,0x3afc3ab5,0x3b953ba0,0x351d34d5,
0x3a993add,0x3887381d,0x3be63bea,0x311530b2,0x39fe3a4f,0x394d38ec,0x3bdd3be2,0x31db3179,0x394d39a8,0x39fe39a8,0x3bd43bd9,0x32a1323e,0x388738ec,0x3a993a4f,0x3bc93bce,0x33653303,
0x3ad63b0e,0x3828378b,0x3bf53bf6,0x2eaa2e46,0x3a563a99,0x38e23887,0x3bf23bf4,0x2f722f0e,0x39c33a0f,0x398d393a,0x3bef3bf1,0x301d2fd6,0x391d3972,0x3a2739dc,0x3bec3bed,0x3080304e,
0xb0b2aa48,0x3bea3bfe,0x3913395f,0x3a2f39ed,0xb564b3c6,0x3b883bc3,0x387238c4,0x3aa73a6d,0xb81db6d7,0x3add3b3b,0x378b381d,0x3b0e3add,0xb95fb8c4,0x39ed3a6d,0x361f36d7,0x3b643b3b,
0xa97f2a48,0x3bfe3bfe,0x39b139ed,0x399f395f,0xb334b04e,0x3bcb3bed,0x39303972,0x3a1739dc,0xb665b505,0x3b553b99,0x38a638ec,0x3a833a4f,0xb87cb7b7,0x3aa03b02,0x3812385d,0x3ae33ab5,
0x2bd930b2,0x3bfc3bea,0x3a3f3a6d,0x390038c4,0xaf0ea648,0x3bf43bff,0x39dc3a0f,0x3972393a,0xb475b23e,0x3baf3bd9,0x397239a8,0x39dc39a8,0xb705b5c2,0x3b303b77,0x3900393a,0x3a3f3a0f,
0x314733c6,0x3be43bc3,0x3abc3add,0x3852381d,0x1e482d7e,0x3c003bf8,0x3a743a99,0x38ba3887,0xb0e4acb5,0x3be83bfa,0x3a273a4f,0x391d38ec,0xb4edb365,0x3b9d3bc9,0x39d439fe,0x397b394d,
0x34443564,0x3bb63b88,0x3b253b3b,0x373236d7,0x2fd6323e,0x3bf13bd9,0x3af63b0e,0x37e3378b,0xa6482a48,0x3bff3bfe,0x3ac23add,0x3848381d,0xb179ae46,0x3be23bf6,0x3a8a3aa7,0x389b3872,
0x35da36d7,0x3b723b3b,0x3b7b3b88,0x35ab3564,0x339634d5,0x3bc63ba0,0x3b5f3b6e,0x363735f1,0x2eaa3179,0x3bf53be2,0x3b413b50,0x36c1367c,0xa7da28b6,0x3bff3bff,0x3b203b30,0x37483705,
0x375e381d,0x3b1a3add,0x3bbc3bc3,0x341433c6,0x3593367c,0x3b803b50,0x3baf3bb6,0x34753444,0x336534a5,0x3bc93ba8,0x3ba03ba8,0x34d534a5,0x2f0e3179,0x3bf43be2,0x3b913b99,0x35343505,
0x386738c4,0x3aae3a6d,0x3be83bea,0x30e430b2,0x37483807,0x3b203ae9,0x3be43be6,0x31473115,0x35ab367c,0x3b7b3b50,0x3be03be2,0x31aa3179,0x33f734d5,0x3bc03ba0,0x3bdb3bdd,0x320d31db,
0xba6db9ed,0x38c4395f,0x34a53564,0x3ba83b88,0xbb3bbadd,0x36d7381d,0x323e33c6,0x3bd93bc3,0xbbc3bb88,0x33c63564,0x2e4630b2,0x3bf63bea,0xbbfebbea,0x2a4830b2,0x2a48,0x3c003bfe,
0xb99fb913,0x39b13a2f,0x36ee378b,0x3b363b0e,0xba92ba1f,0x38913927,0x35ab364e,0x3b7b3b5a,0xbb4bbaf6,0x369337e3,0x345d3505,0x3bb23b99,0xbbc6bb91,0x33963534,0x320d3365,0x3bdb3bc9,
0xb8b0b81d,0x3a7c3add,0x388738c4,0x3a993a6d,0xb9bab93a,0x39963a0f,0x38073848,0x3ae93ac2,0xba99ba2f,0x38873913,0x3705378b,0x3b303b0e,0xbb46baf6,0x36aa37e3,0x35f1367c,0x3b6e3b50,
0xb748b61f,0x3b203b64,0x397b39a8,0x39d439a8,0xb8bab832,0x3a743ad0,0x391d394d,0x3a2739fe,0xb9b1b93a,0x399f3a0f,0x38ba38ec,0x3a743a4f,0xba83ba1f,0x38a63927,0x38523887,0x3abc3a99,
0xb505b3c6,0x3b993bc3,0x3a4f3a6d,0x38ec38c4,0xb732b61f,0x3b253b64,0x3a0f3a2f,0x393a3913,0xb89bb81d,0x3a8a3add,0x39cb39ed,0x3984395f,0xb984b913,0x39cb3a2f,0x398439a8,0x39cb39a8,
0xb147ae46,0x3be43bf6,0x3afc3b0e,0x37cd378b,0xb4bdb365,0x3ba43bc9,0x3ad63ae9,0x38283807,0xb6c1b5c2,0x3b413b77,0x3aae3ac2,0x38673848,0xb852b7b7,0x3abc3b02,0x3a833a99,0x38a63887,
0xa2482a48,0x3c003bfe,0x3b803b88,0x35933564,0xb04eacb5,0x3bed3bfa,0x3b6e3b77,0x35f135c2,0xb414b23e,0x3bbc3bd9,0x3b5a3b64,0x364e361f,0xb5f1b505,0x3b6e3b99,0x3b463b50,0x36aa367c,
0x3080323e,0x3bec3bd9,0x3bd63bd9,0x326f323e,0x27da2d7e,0x3bff3bf8,0x3bd13bd4,0x32d232a1,0xad1aa648,0x3bf93bff,0x3bcb3bce,0x33343303,0xb20db04e,0x3bdb3bed,0x3bc63bc9,0x33963365,
0x2a482a48,0xbbfebbfe,0x3bd93bfe,0x323e2a48,0x2a482a48,0xbbfebbfe,0x3b0e3b88,0x378b3564,0x2a482a48,0xbbfebbfe,0x39a83a6d,0x39a838c4,0x2a482a48,0xbbfebbfe,0x378b38c4,0x3b0e3a6d,
0x3be83bfe,0x30e42a48,0x3bd63bfe,0x326f2a48,0x3b7b3bbc,0x35ab3414,0x3afc3b80,0x37cd3593,0x3abc3b25,0x38523732,0x397b3a4f,0x39d438ec,0x39b13a3f,0x399f3900,0x36ee3887,0x3b363a99,
0x3be63bfe,0x31152a48,0x3bd43bfe,0x32a12a48,0x3b6e3bb6,0x35f13444,0x3ae93b77,0x380735c2,0x3a993b0e,0x3887378b,0x394d3a2f,0x39fe3913,0x39723a0f,0x39dc393a,0x364e3848,0x3b5a3ac2,
0x3be43bfe,0x31472a48,0x3bd13bfe,0x32d22a48,0x3b5f3baf,0x36373475,0x3ad63b6e,0x382835f1,0x3a743af6,0x38ba37e3,0x391d3a0f,0x3a27393a,0x393039dc,0x3a173972,0x35ab3807,0x3b7b3ae9,
0x3be23bfe,0x31792a48,0x3bce3bfe,0x33032a48,0x3b503ba8,0x367c34a5,0x3ac23b64,0x3848361f,0x3a4f3add,0x38ec381d,0x38ec39ed,0x3a4f395f,0x38ec39a8,0x3a4f39a8,0x3505378b,0x3b993b0e,
0x3be03bfe,0x31aa2a48,0x3bcb3bfe,0x33342a48,0x3b413ba0,0x36c134d5,0x3aae3b5a,0x3867364e,0x3a273ac2,0x391d3848,0x38ba39cb,0x3a743984,0x38a63972,0x3a8339dc,0x345d3705,0x3bb23b30,
0x3bdd3bfe,0x31db2a48,0x3bc93bfe,0x33652a48,0x3b303b99,0x37053505,0x3a993b50,0x3887367c,0x39fe3aa7,0x394d3872,0x388739a8,0x3a9939a8,0x385d393a,0x3ab53a0f,0x3365367c,0x3bc93b50,
0x3bdb3bfe,0x320d2a48,0x3bc63bfe,0x33962a48,0x3b203b91,0x37483534,0x3a833b46,0x38a636aa,0x39d43a8a,0x397b389b,0x38523984,0x3abc39cb,0x38123900,0x3ae33a3f,0x320d35f1,0x3bdb3b6e,
0x2a482a48,0xbbfebbfe,0x323e3564,0x3bd93b88,0x2a482a48,0xbbfebbfe,0xae462a48,0x3bf63bfe,0x2a482a48,0xbbfebbfe,0xb61fb3c6,0x3b643bc3,0x2a482a48,0xbbfebbfe,0xb913b81d,0x3a2f3add,
0x38673913,0x3aae3a2f,0x308034a5,0x3bec3ba8,0x35da375e,0x3b723b1a,0xb147a248,0x3be43c00,0x31473444,0x3be43bb6,0xb748b505,0x3b203b99,0xa97f2bd9,0x3bfe3bfc,0xb99fb8b0,0x39b13a7c,
0x380738c4,0x3ae93a6d,0x2d7e33c6,0x3bf83bc3,0x34d5367c,0x3ba03b50,0xb365acb5,0x3bc93bfa,0x2d7e323e,0x3bf83bd9,0xb832b61f,0x3ad03b64,0xb04ea648,0x3bed3bff,0xba1fb93a,0x39273a0f,
0x37483872,0x3b203aa7,0x27da323e,0x3bff3bd9,0x33963593,0x3bc63b80,0xb4bdb04e,0x3ba43bed,0x1e482fd6,0x3c003bf1,0xb8bab732,0x3a743b25,0xb334af0e,0x3bcb3bf4,0xba92b9ba,0x38913996,
0x367c381d,0x3b503add,0xa64830b2,0x3bff3bea,0x317934a5,0x3be23ba8,0xb5c2b23e,0x3b773bd9,0xacb52a48,0x3bfa3bfe,0xb93ab81d,0x3a0f3add,0xb505b23e,0x3b993bd9,0xbaf6ba2f,0x37e33913,
0x35ab378b,0x3b7b3b0e,0xad1a2e46,0x3bf93bf6,0x2eaa3365,0x3bf53bc9,0xb6c1b414,0x3b413bbc,0xb0e4a648,0x3be83bff,0xb9b1b89b,0x399f3a8a,0xb665b475,0x3b553baf,0xbb4bba99,0x36933887,
0x34d536d7,0x3ba03b3b,0xb04e2a48,0x3bed3bfe,0x28b63179,0x3bff3be2,0xb7b7b505,0x3b023b99,0xb365ae46,0x3bc93bf6,0xba1fb913,0x39273a2f,0xb7b7b5c2,0x3b023b77,0xbb91baf6,0x353437e3,
0x33f7361f,0x3bc03b64,0xb20d8000,0x3bdb3c00,0xa7da2f0e,0x3bff3bf4,0xb852b5f1,0x3abc3b6e,0xb4edb179,0x3b9d3be2,0xba83b984,0x38a639cb,0xb87cb705,0x3aa03b30,0xbbc6bb46,0x339636aa,
0x2a482a48,0xbbfebbfe,0xbaa7b9ed,0x3872395f,0x2a482a48,0xbbfebbfe,0xbba8bb3b,0x34a536d7,0x2a482a48,0xbbfebbfe,0xbc00bbea,0x800030b2,0x2a482a48,0xbbfebbfe,0xbba8bbea,0xb4a5b0b2,
0xb3f7b0b2,0x3bc03bea,0xbb14ba6d,0x377538c4,0xb71bb593,0x3b2b3b80,0xbbe0bb91,0x31aa3534,0xb8f6b848,0x3a473ac2,0xbbefbbff,0xb01d2648,0xba27b996,0x391d39ba,0xbb41bbaf,0xb6c1b475,
0xb593b3c6,0x3b803bc3,0xbb6ebadd,0x35f1381d,0xb85db732,0x3ab53b25,0xbbfcbbce,0x2bd93303,0xb9bab913,0x39963a2f,0xbbbcbbf6,0xb414ae46,0xbad0ba4f,0x383238ec,0xbab5bb50,0xb85db67c,
0xb71bb564,0x3b2b3b88,0xbbb2bb3b,0x345d36d7,0xb91db85d,0x3a273ab5,0xbbfdbbf4,0xab112f0e,0xba65b9cb,0x38ce3984,0xbb69bbce,0xb608b303,0xbb55bae9,0x36653807,0xba07bad0,0xb943b832,
0xb848b6d7,0x3ac23b3b,0xbbe2bb88,0x31793564,0xb9cbb913,0x39843a2f,0xbbe2bc00,0xb1798000,0xbaf6ba6d,0x37e338c4,0xbaf6bb88,0xb7e3b564,0xbbb6bb64,0x3444361f,0xb93aba2f,0xba0fb913,
0xb8f6b81d,0x3a473add,0xbbfbbbc3,0x2c5133c6,0xba65b9ba,0x38ce3996,0xbbabbbf4,0xb48daf0e,0xbb69baf6,0x360837e3,0xba65bb25,0xb8ceb732,0xbbefbbbc,0x301d3414,0xb852b972,0xbabcb9dc,
0xb996b8c4,0x39ba3a6d,0xbbffbbea,0xa8b630b2,0xbae9ba4f,0x380738ec,0xbb5abbce,0xb64eb303,0xbbbcbb64,0x3414361f,0xb9babaa7,0xb996b872,0xbc00bbf1,0xa2482fd6,0xb6aab89b,0xbb46ba8a,
0xba27b95f,0x391d39ed,0xbbecbbfe,0xb0802a48,0xbb55bad0,0x36653832,0xbaf0bb91,0xb7f9b534,0xbbefbbb6,0x301d3444,0xb8f6ba0f,0xba47b93a,0xbbe8bc00,0xb0e4a248,0xb48db75e,0xbbabbb1a,
0x2a482a48,0xbbfebbfe,0xbaa7bb3b,0xb872b6d7,0x2a482a48,0xbbfebbfe,0xb913b9ed,0xba2fb95f,0x2a482a48,0xbbfebbfe,0xb61fb81d,0xbb64badd,0x2a482a48,0xbbfebbfe,0xae46b3c6,0xbbf6bbc3,
0xbb14baa7,0x37753872,0xb9e5baa7,0xb969b872,0xbbb2bb6e,0x345d35f1,0xb7f9b900,0xbaf0ba3f,0xbbfbbbe2,0x2c513179,0xb2d2b5c2,0xbbd1bb77,0xbbecbbff,0xb080a8b6,0x2de2abd9,0xbbf7bbfc,
0xbb91bb3b,0x353436d7,0xb900b9ed,0xba3fb95f,0xbbf4bbce,0x2f0e3303,0xb593b7e3,0xbb80baf6,0xbbf4bc00,0xaf0e0000,0xa8b6b23e,0xbbffbbd9,0xbb91bbce,0xb534b303,0x34752fd6,0xbbafbbf1,
0xbbe0bba8,0x31aa34a5,0xb7f9b913,0xbaf0ba2f,0xbbfdbbfc,0xab112bd9,0xb20db593,0xbbdbbb80,0xbbabbbe2,0xb48db179,0x3080a648,0xbbecbbff,0xbaf0bb5a,0xb7f9b64e,0x374834d5,0xbb20bba0,
0xbbffbbea,0x264830b2,0xb5c2b81d,0xbb77badd,0xbbcebbf6,0xb303ae46,0xa648b23e,0xbbffbbd9,0xbb25bb88,0xb732b564,0x350530b2,0xbb99bbea,0xba0fbaa7,0xb93ab872,0x38ec378b,0xba4fbb0e,
0xbbefbc00,0xb01d8000,0xb2d2b61f,0xbbd1bb64,0xbb69bbbc,0xb608b414,0x3080a8b6,0xbbecbbff,0xba65baf6,0xb8ceb7e3,0x37a13505,0xbb08bb99,0xb8f6b9ba,0xba47b996,0x3a073900,0xb943ba3f,
0xbbafbbea,0xb475b0b2,0xabd9b3c6,0xbbfcbbc3,0xbad0bb50,0xb832b67c,0x34d52fd6,0xbba0bbf1,0xb972ba2f,0xb9dcb913,0x3900378b,0xba3fbb0e,0xb75eb89b,0xbb1aba8a,0x3ae93a0f,0xb807b93a,
0xbb41bba8,0xb6c1b4a5,0x2de2ae46,0xbbf7bbf6,0xba07bab5,0xb943b85d,0x37483475,0xbb20bbaf,0xb852b93a,0xbabcba0f,0x3a0738ec,0xb943ba4f,0xb48db6aa,0xbbabbb46,0x3b8c3ae9,0xb54cb807,
0x3bea3bfe,0xb0b2aa48,0x3913395f,0xba2fb9ed,0x3b883bc3,0xb564b3c6,0x387238c4,0xbaa7ba6d,0x3add3b3b,0xb81db6d7,0x378b381d,0xbb0ebadd,0x39ed3a6d,0xb95fb8c4,0x361f36d7,0xbb64bb3b,
0x3bc63bea,0xb396b0b2,0x387c38c4,0xbaa0ba6d,0x3b4b3b91,0xb693b534,0x37cd3832,0xbafcbad0,0x3a923af6,0xb891b7e3,0x36933732,0xbb4bbb25,0x399f3a1f,0xb9b1b927,0x354c35f1,0xbb8cbb6e,
0x3b913bc3,0xb534b3c6,0x37b7381d,0xbb02badd,0x3b023b50,0xb7b7b67c,0x36aa3732,0xbb46bb25,0x3a3f3aa7,0xb900b872,0x3593361f,0xbb80bb64,0x394d39cb,0xb9feb984,0x34753505,0xbbafbb99,
0x3b4b3b88,0xb693b564,0x366536d7,0xbb55bb3b,0x3aae3b02,0xb867b7b7,0x357c35f1,0xbb84bb6e,0x39e53a4f,0xb969b8ec,0x348d3505,0xbbabbb99,0x38f63972,0xba47b9dc,0x33343414,0xbbcbbbbc,
0x3af63b3b,0xb7e3b6d7,0x35053564,0xbb99bb88,0x3a4f3aa7,0xb8ecb872,0x344434a5,0xbbb6bba8,0x398439ed,0xb9cbb95f,0x330333c6,0xbbcebbc3,0x389b3913,0xba8aba2f,0x3179323e,0xbbe2bbd9,
0x3a923add,0xb891b81d,0x333433c6,0xbbcbbbc3,0x39e53a3f,0xb969b900,0x320d32a1,0xbbdbbbd4,0x391d3984,0xba27b9cb,0x30e43179,0xbbe8bbe2,0x383d38b0,0xbac9ba7c,0x2f72304e,0xbbf2bbed,
0x3a1f3a6d,0xb927b8c4,0x304e30b2,0xbbedbbea,0x397239cb,0xb9dcb984,0x2f0e2fd6,0xbbf4bbf1,0x38b03913,0xba7cba2f,0x2d7e2e46,0xbbf8bbf6,0x37b73848,0xbb02bac2,0x2bd92cb5,0xbbfcbbfa,
0x399f39ed,0xb9b1b95f,0x297f2a48,0xbbfebbfe,0x38f6394d,0xba47b9fe,0x27da28b6,0xbbffbbff,0x383d389b,0xbac9ba8a,0x24b62648,0xbc00bbff,0x36ee37b7,0xbb36bb02,0x1e482248,0xbc00bc00,
0x38c4395f,0xba6db9ed,0x34a53564,0xbba8bb88,0x36d7381d,0xbb3bbadd,0x323e33c6,0xbbd9bbc3,0x33c63564,0xbbc3bb88,0x2e4630b2,0xbbf6bbea,0x2a4830b2,0xbbfebbea,0x2a48,0xbc00bbfe,
0x387c3913,0xbaa0ba2f,0x33f734a5,0xbbc0bba8,0x366537b7,0xbb55bb02,0x314732a1,0xbbe4bbd4,0x33343505,0xbbcbbb99,0x2d1a2fd6,0xbbf9bbf1,0x297f304e,0xbbfebbed,0x9e4828b6,0xbc00bbff,
0x383238c4,0xbad0ba6d,0x32a133c6,0xbbd4bbc3,0x35f13732,0xbb6ebb25,0x304e3179,0xbbedbbe2,0x32a134a5,0xbbd4bba8,0x2bd92e46,0xbbfcbbf6,0x28b62fd6,0xbbffbbf1,0xa2482648,0xbc00bbff,
0x37cd3872,0xbafcbaa7,0x3147323e,0xbbe4bbd9,0x357c36aa,0xbb84bb46,0x2eaa304e,0xbbf5bbed,0x320d3444,0xbbdbbbb6,0x297f2cb5,0xbbfebbfa,0x27da2f0e,0xbbffbbf4,0xa4b62248,0xbc00bc00,
0x3732381d,0xbb25badd,0x2fd630b2,0xbbf1bbea,0x3505361f,0xbb99bb64,0x2cb52e46,0xbbfabbf6,0x317933c6,0xbbe2bbc3,0x26482a48,0xbbffbbfe,0x26482e46,0xbbffbbf6,0xa6480000,0xbbffbc00,
0x3693378b,0xbb4bbb0e,0x2d1a2e46,0xbbf9bbf6,0x348d3593,0xbbabbb80,0x297f2bd9,0xbbfebbfc,0x30e43303,0xbbe8bbce,0x1e482648,0xbc00bbff,0x24b62d7e,0xbc00bbf8,0xa7daa248,0xbbffbc00,
0x35f136d7,0xbb6ebb3b,0x28b62a48,0xbbffbbfe,0x34143505,0xbbbcbb99,0x22482648,0xbc00bbff,0x304e323e,0xbbedbbd9,0xa2480000,0xbc00bc00,0x22482cb5,0xbc00bbfa,0xa8b6a648,0xbbffbbff,
0x354c361f,0xbb8cbb64,0x9e480000,0xbc00bc00,0x33343475,0xbbcbbbaf,0xa4b6a248,0xbc00bc00,0x2f723179,0xbbf2bbe2,0xa7daa648,0xbbffbbff,0x1e482bd9,0xbc00bbfc,0xa97fa8b6,0xbbfebbff,
0x3bfeaa48,0x2a48bbfe,0x39a8aa48,0xb9a8bbfe,0x3bc33bea,0x33c630b2,0x3a2f39ed,0xb913b95f,0x3b3b3b88,0x36d73564,0x3aa73a6d,0xb872b8c4,0x3a6d3add,0x38c4381d,0x3b0e3add,0xb78bb81d,
0x3bfdaa48,0xab11bbfe,0x3909aa48,0xba37bbfe,0x3bef3bff,0x301d28b6,0x398d394d,0xb9c3b9fe,0x3b9d3bce,0x34ed3303,0x3a0739cb,0xb943b984,0x3b083b5a,0x37a1364e,0x3a743a3f,0xb8bab900,
0x3be6aa48,0xb115bbfe,0x385daa48,0xbab5bbfe,0x3c003bfa,0x2248acb5,0x38d8389b,0xba5eba8a,0x3bdd3bf6,0x31db2e46,0x394d3913,0xb9feba2f,0x3b803bb6,0x35933444,0x39ba3984,0xb996b9cb,
0x3bb9aa48,0xb42cbbfe,0x3748aa48,0xbb20bbfe,0x3bf53bdd,0xaeaab1db,0x381237b7,0xbae3bb02,0x3bfd3bff,0x2b11a648,0x387c3848,0xbaa0bac2,0x3bd13bed,0x32d2304e,0x38e238b0,0xba56ba7c,
0x3b77aa48,0xb5c2bbfe,0x35c2aa48,0xbb77bbfe,0x3bce3ba8,0xb303b4a5,0x367c361f,0xbb50bb64,0x3bfa3bea,0xacb5b0b2,0x373236d7,0xbb25bb3b,0x3bfa3c00,0x2cb58000,0x37e3378b,0xbaf6bb0e,
0x3b20aa48,0xb748bbfe,0x342caa48,0xbbb9bbfe,0x3b8c3b5a,0xb54cb64e,0x34bd3475,0xbba4bbaf,0x3bd63bb6,0xb26fb444,0x354c3505,0xbb8cbb99,0x3bfb3bed,0xac51b04e,0x35da3593,0xbb72bb80,
0x3ab5aa48,0xb85dbbfe,0x3115aa48,0xbbe6bbfe,0x3b303af6,0xb705b7e3,0x31db3179,0xbbddbbe2,0x3b913b64,0xb534b61f,0x32a1323e,0xbbd4bbd9,0x3bd43bb6,0xb2a1b444,0x33653303,0xbbc9bbce,
0x3a37aa48,0xb909bbfe,0x2b11aa48,0xbbfdbbfe,0x3abc3a7c,0xb852b8b0,0x2c512bd9,0xbbfbbbfc,0x3b2b3af6,0xb71bb7e3,0x2d1a2cb5,0xbbf9bbfa,0x3b843b5a,0xb57cb64e,0x2de22d7e,0xbbf7bbf8,
0x395f39ed,0x39ed395f,0x3b643b3b,0xb61fb6d7,0x381d38c4,0x3add3a6d,0x3ba83b88,0xb4a5b564,0x356436d7,0x3b883b3b,0x3bd93bc3,0xb23eb3c6,0x30b233c6,0x3bea3bc3,0x3bf63bea,0xae46b0b2,
0x3a373aa7,0x39093872,0x3ad63aa7,0xb828b872,0x393039ba,0x3a173996,0x3b2b3b02,0xb71bb7b7,0x37f9389b,0x3af03a8a,0x3b723b50,0xb5dab67c,0x354c36aa,0x3b8c3b46,0x3bab3b91,0xb48db534,
0x3ae93b3b,0x380736d7,0x3a1f39ed,0xb927b95f,0x3a1f3a8a,0x3927389b,0x3a7c3a4f,0xb8b0b8ec,0x392739a8,0x3a1f39a8,0x3ad03aa7,0xb832b872,0x3807389b,0x3ae93a8a,0x3b1a3af6,0xb75eb7e3,
0x3b723ba8,0x35da34a5,0x39433913,0xba07ba2f,0x3ae33b30,0x38123705,0x399f3972,0xb9b1b9dc,0x3a273a8a,0x391d389b,0x39f639cb,0xb956b984,0x394339ba,0x3a073996,0x3a473a1f,0xb8f6b927,
0x3bce3bea,0x330330b2,0x3848381d,0xbac2badd,0x3b773ba8,0x35c234a5,0x389b3872,0xba8abaa7,0x3af63b3b,0x37e336d7,0x38ec38c4,0xba4fba6d,0x3a4f3aa7,0x38ec3872,0x393a3913,0xba0fba2f,
0x3bfb3c00,0x2c510000,0x3665361f,0xbb55bb64,0x3bd63bed,0x326f304e,0x36ee36aa,0xbb36bb46,0x3b8c3bb6,0x354c3444,0x37753732,0xbb14bb25,0x3b203b5a,0x3748364e,0x37f937b7,0xbaf0bb02,
0x3bf83bea,0xad7eb0b2,0x341433c6,0xbbbcbbc3,0x3bff3bff,0x28b6a648,0x34753444,0xbbafbbb6,0x3be63bf6,0x31152e46,0x34d534a5,0xbba0bba8,0x3baf3bce,0x34753303,0x35343505,0xbb91bb99,
0x3bc63ba8,0xb396b4a5,0x2eaa2e46,0xbbf5bbf6,0x3bef3bdd,0xb01db1db,0x2f722f0e,0xbbf2bbf4,0x3c003bfa,0xa4b6acb5,0x301d2fd6,0xbbefbbf1,0x3bf73bff,0x2de228b6,0x3080304e,0xbbecbbed,
0x3bfd3bfe,0xab112a48,0x3a37395f,0x390939ed,0x3bb93be6,0xb42cb115,0x3b723ae9,0x35da3807,0x3b203b77,0xb748b5c2,0x3bfb3bce,0x2c513303,0x3a373ab5,0xb909b85d,0x3bc63bf8,0xb396ad7e,
0x3bff3bea,0x28b630b2,0x39ba38c4,0x39963a6d,0x3bdd3bfa,0xb1dbacb5,0x3b303a8a,0x3705389b,0x3b5a3ba8,0xb64eb4a5,0x3bed3ba8,0x304e34a5,0x3a7c3af6,0xb8b0b7e3,0x3bdd3bff,0xb1dba648,
0x3bef3bc3,0x301d33c6,0x3930381d,0x3a173add,0x3bf53c00,0xaeaa2248,0x3ae33a1f,0x38123927,0x3b8c3bce,0xb54cb303,0x3bd63b77,0x326f35c2,0x3abc3b30,0xb852b705,0x3bef3bff,0xb01d28b6,
0x3bce3b88,0x33033564,0x389b36d7,0x3a8a3b3b,0x3bff3bf6,0xa6482e46,0x3a8a39a8,0x389b39a8,0x3bb63bea,0xb444b0b2,0x3bb63b3b,0x344436d7,0x3af63b64,0xb7e3b61f,0x3bfa3bf6,0xacb52e46,
0x3b9d3b3b,0x34ed36d7,0x37f93564,0x3af03b88,0x3bfd3bdd,0x2b1131db,0x3a273927,0x391d3a1f,0x3bd63bfa,0xb26facb5,0x3b8c3af6,0x354c37e3,0x3b2b3b91,0xb71bb534,0x3c003be6,0xa4b63115,
0x3b5a3add,0x364e381d,0x36aa33c6,0x3b463bc3,0x3bed3bb6,0x304e3444,0x39ba389b,0x39963a8a,0x3bed3c00,0xb04e8000,0x3b5a3aa7,0x364e3872,0x3b5a3bb6,0xb64eb444,0x3bff3bce,0x28b63303,
0x3b083a6d,0x37a138c4,0x354c30b2,0x3b8c3bea,0x3bd13b80,0x32d23593,0x39433807,0x3a073ae9,0x3bfb3bfa,0xac512cb5,0x3b203a4f,0x374838ec,0x3b843bd4,0xb57cb2a1,0x3bf73baf,0x2de23475,
0x3aa739ed,0x3872395f,0x33c62a48,0x3bc33bfe,0x3ba83b3b,0x34a536d7,0x38c436d7,0x3a6d3b3b,0x3c003bea,0x30b2,0x3add39ed,0x381d395f,0x3ba83bea,0xb4a5b0b2,0x3bea3b88,0x30b23564,
0x390939a8,0xba37b9a8,0x3ad63b64,0xb828b61f,0x3748385d,0xbb20bab5,0x39433a1f,0xba07b927,0x342c35c2,0xbbb9bb77,0x36653848,0xbb55bac2,0x2b113115,0xbbfdbbe6,0x2eaa3414,0xbbf5bbbc,
0x394d39ed,0xb9feb95f,0x3b023b88,0xb7b7b564,0x37b7389b,0xbb02ba8a,0x39723a4f,0xb9dcb8ec,0x3475361f,0xbbafbb64,0x36aa3872,0xbb46baa7,0x2bd93179,0xbbfcbbe2,0x2f0e3444,0xbbf4bbb6,
0x398d3a2f,0xb9c3b913,0x3b2b3ba8,0xb71bb4a5,0x381238d8,0xbae3ba5e,0x399f3a7c,0xb9b1b8b0,0x34bd367c,0xbba4bb50,0x36ee389b,0xbb36ba8a,0x2c5131db,0xbbfbbbdd,0x2f723475,0xbbf2bbaf,
0x39cb3a6d,0xb984b8c4,0x3b503bc3,0xb67cb3c6,0x38483913,0xbac2ba2f,0x39cb3aa7,0xb984b872,0x350536d7,0xbb99bb3b,0x373238c4,0xbb25ba6d,0x2cb5323e,0xbbfabbd9,0x2fd634a5,0xbbf1bba8,
0x3a073aa7,0xb943b872,0x3b723bd9,0xb5dab23e,0x387c394d,0xbaa0b9fe,0x39f63ad0,0xb956b832,0x354c3732,0xbb8cbb25,0x377538ec,0xbb14ba4f,0x2d1a32a1,0xbbf9bbd4,0x301d34d5,0xbbefbba0,
0x3a3f3add,0xb900b81d,0x3b913bea,0xb534b0b2,0x38b03984,0xba7cb9cb,0x3a1f3af6,0xb927b7e3,0x3593378b,0xbb80bb0e,0x37b73913,0xbb02ba2f,0x2d7e3303,0xbbf8bbce,0x304e3505,0xbbedbb99,
0x3a743b0e,0xb8bab78b,0x3bab3bf6,0xb48dae46,0x38e239ba,0xba56b996,0x3a473b1a,0xb8f6b75e,0x35da37e3,0xbb72baf6,0x37f9393a,0xbaf0ba0f,0x2de23365,0xbbf7bbc9,0x30803534,0xbbecbb91,
0x3aa73b3b,0xb872b6d7,0x3bc33bfe,0xb3c6aa48,0x391339ed,0xba2fb95f,0x3a6d3b3b,0xb8c4b6d7,0x361f381d,0xbb64badd,0x381d395f,0xbaddb9ed,0x2e4633c6,0xbbf6bbc3,0x30b23564,0xbbeabb88,
0x3be8aa48,0x30e4bbfe,0x3867aa48,0x3aaebbfe,0x3b7b3bbc,0x35ab3414,0x345d36aa,0x3bb23b46,0x3abc3b25,0x38523732,0xa7da2fd6,0x3bff3bf1,0x39b13a3f,0x399f3900,0xb54cb1db,0x3b8c3bdd,
0x3bbcaa48,0x3414bbfe,0x375eaa48,0x3b1abbfe,0x3b1a3b77,0x375e35c2,0x31153505,0x3be63b99,0x3a1f3aa7,0x39273872,0xb1158000,0x3be63c00,0x38d83984,0x3a5e39cb,0xb75eb505,0x3b1a3b99,
0x3b7baa48,0x35abbbfe,0x35daaa48,0x3b72bbfe,0x3aa03b1a,0x387c375e,0x297f32a1,0x3bfe3bd4,0x39693a0f,0x39e5393a,0xb48dafd6,0x3bab3bf1,0x37cd38b0,0x3afc3a7c,0xb8a6b705,0x3a833b30,
0x3b25aa48,0x3732bbfe,0x3444aa48,0x3bb6bbfe,0x3a0f3aa7,0x393a3872,0xacb52e46,0x3bfa3bf6,0x389b395f,0x3a8a39ed,0xb67cb3c6,0x3b503bc3,0x35c2378b,0x3b773b0e,0xb984b872,0x39cb3aa7,
0x3abcaa48,0x3852bbfe,0x3147aa48,0x3be4bbfe,0x39693a1f,0x39e53927,0xb20da248,0x3bdb3c00,0x3775389b,0x3b143a8a,0xb828b5c2,0x3ad63b77,0x33343593,0x3bcb3b80,0xba47b94d,0x38f639fe,
0x3a3faa48,0x3900bbfe,0x2bd9aa48,0x3bfcbbfe,0x38b03984,0x3a7c39cb,0xb4d5afd6,0x3ba03bf1,0x3593378b,0x3b803b0e,0xb900b78b,0x3a3f3b0e,0x2d7e3303,0x3bf83bce,0xbae9ba0f,0x3807393a,
0x39b1aa48,0x399fbbfe,0xa97faa48,0x3bfebbfe,0x37cd38d8,0x3afc3a5e,0xb693b365,0x3b4b3bc9,0x333435c2,0x3bcb3b77,0xb9c3b89b,0x398d3a8a,0xab112d7e,0x3bfd3bf8,0xbb69bab5,0x3608385d,
0x3913aa48,0x3a2fbbfe,0xb0b2aa48,0x3beabbfe,0x361f381d,0x3b643add,0xb81db564,0x3add3b88,0x2e4633c6,0x3bf63bc3,0xba6db95f,0x38c439ed,0xb23eaa48,0x3bd93bfe,0xbbc3bb3b,0x33c636d7,
0x38673913,0x3aae3a2f,0xb8ceb78b,0x3a653b0e,0x35da375e,0x3b723b1a,0xba83b9ba,0x38a63996,0x31473444,0x3be43bb6,0xbb9dbb25,0x34ed3732,0xa97f2bd9,0x3bfe3bfc,0xbc00bbe6,0x1e483115,
0x36aa381d,0x3b463add,0xb9bab8c4,0x39963a6d,0x32a13505,0x3bd43b99,0xbb30ba8a,0x3705389b,0xa2482e46,0x3c003bf6,0xbbedbba8,0x304e34a5,0xb365afd6,0x3bc93bf1,0xbbddbbff,0xb1dba648,
0x345d361f,0x3bb23b64,0xba83b9a8,0x38a639a8,0x297f3115,0x3bfe3be6,0xbbabbb30,0x348d3705,0xb20dacb5,0x3bdb3bfa,0xbbfebbf1,0xa97f2fd6,0xb693b4d5,0x3b4b3ba0,0xbb72bbd4,0xb5dab2a1,
0x2fd633c6,0x3bf13bc3,0xbb25ba6d,0x373238c4,0xafd68000,0x3bf13c00,0xbbf1bba8,0x2fd634a5,0xb5c2b3c6,0x3b773bc3,0xbbcebbfe,0xb303aa48,0xb89bb78b,0x3a8a3b0e,0xbac2bb64,0xb848b61f,
0xa7da2e46,0x3bff3bf6,0xbb9dbb0e,0x34ed378b,0xb48db115,0x3bab3be6,0xbbfebbed,0xa97f304e,0xb828b67c,0x3ad63b50,0xbb5fbbce,0xb637b303,0xb9c3b900,0x398d3a3f,0xb9d4bab5,0xb97bb85d,
0xb1dbaa48,0x3bdd3bfe,0xbbe6bb88,0x31153564,0xb705b505,0x3b303b99,0xbbd4bbff,0xb2a1a648,0xb94db872,0x39fe3aa7,0xbab5bb64,0xb85db61f,0xbab5ba0f,0x385d393a,0xb8b0b9cb,0xba7cb984,
0xb54cb23e,0x3b8c3bd9,0xbc00bbd9,0x1e48323e,0xb8a6b75e,0x3a833b1a,0xbb72bbdd,0xb5dab1db,0xba47b984,0x38f639cb,0xb9d4bac2,0xb97bb848,0xbb69bae9,0x36083807,0xb6c1b8b0,0xbb41ba7c,
0xb78bb564,0x3b0e3b88,0xbbeabbfe,0xb0b22a48,0xb9a8b8c4,0x39a83a6d,0xbaddbb88,0xb81db564,0xbb0eba6d,0x378b38c4,0xb8c4b9ed,0xba6db95f,0xbbd9bb88,0x323e3564,0xb3c6b6d7,0xbbc3bb3b,
0x31a131a8,0x2f2d3000,0x31a10000,0x2f2d3000,0x316a318c,0x2d552e49,0x316a318c,0x2d552e49,0x30fd313a,0x2a922c54,0x30fd313a,0x2a922c54,0x305f30b4,0x2470286a,0x305f30b4,0x2470286a,
0x316a31a8,0xb0fdb000,0x316a8000,0xb0fdb000,0x2f2d30b4,0xb1a1b18c,0x2f2d30b4,0xb1a1b18c,0x24702c54,0xb05fb13a,0x24702c54,0xb05fb13a,0xad55a86a,0xaa92ae49,0xad55a86a,0xaa92ae49,
0x30fd31a8,0xaa92b000,0x30fd0000,0xaa92b000,0x24702e49,0x2f2d286a,0x24702e49,0x2f2d286a,0xb05fac54,0x31a1313a,0xb05fac54,0x31a1313a,0xb16ab18c,0x2d5530b4,0xb16ab18c,0x2d5530b4,
0x305f31a8,0x31a13000,0x305f8000,0x31a13000,0xad55286a,0x2a9230b4,0xad55286a,0x2a9230b4,0xb16ab13a,0xb0fdac54,0xb16ab13a,0xb0fdac54,0x2470ae49,0xaf2db18c,0x2470ae49,0xaf2db18c,
0x2f2d31a8,0xa4703000,0x2f2d0000,0xa4703000,0xb0fda86a,0xb16ab0b4,0xb0fda86a,0xb16ab0b4,0xaa92b13a,0x2d55ac54,0xaa92b13a,0x2d55ac54,0x31a12e49,0x305f318c,0x31a12e49,0x305f318c,
0x2d5531a8,0xb16ab000,0x2d558000,0xb16ab000,0xb1a1ae49,0x305fa86a,0xb1a1ae49,0x305fa86a,0x2f2dac54,0x2470313a,0x2f2dac54,0x2470313a,0x2a92318c,0xb0fdb0b4,0x2a92318c,0xb0fdb0b4,
0x2a9231a8,0x2d55b000,0x2a928000,0x2d55b000,0xb05fb0b4,0x2470318c,0xb05fb0b4,0x2470318c,0x31a12c54,0xaf2db13a,0x31a12c54,0xaf2db13a,0xb0fd286a,0x316a2e49,0xb0fd286a,0x316a2e49,
0x247031a8,0x305f3000,0x24708000,0x305f3000,0xaa92b18c,0xb0fdae49,0xaa92b18c,0xb0fdae49,0x2d55313a,0x316a2c54,0x2d55313a,0x316a2c54,0xaf2db0b4,0xb1a1a86a,0xaf2db0b4,0xb1a1a86a,
0xa47031a8,0xb05f3000,0xa4708000,0xb05f3000,0x2a92b18c,0x30fdae49,0x2a92b18c,0x30fdae49,0xad55313a,0xb16a2c54,0xad55313a,0xb16a2c54,0x2f2db0b4,0x31a1a86a,0x2f2db0b4,0x31a1a86a,
0xaa9231a8,0xad55b000,0xaa928000,0xad55b000,0x305fb0b4,0xa470318c,0x305fb0b4,0xa470318c,0xb1a12c54,0x2f2db13a,0xb1a12c54,0x2f2db13a,0x30fd286a,0xb16a2e49,0x30fd286a,0xb16a2e49,
0xad5531a8,0x316ab000,0xad558000,0x316ab000,0x31a1ae49,0xb05fa86a,0x31a1ae49,0xb05fa86a,0xaf2dac54,0xa470313a,0xaf2dac54,0xa470313a,0xaa92318c,0x30fdb0b4,0xaa92318c,0x30fdb0b4,
0xaf2d31a8,0x24703000,0xaf2d8000,0x24703000,0x30fda86a,0x316ab0b4,0x30fda86a,0x316ab0b4,0x2a92b13a,0xad55ac54,0x2a92b13a,0xad55ac54,0xb1a12e49,0xb05f318c,0xb1a12e49,0xb05f318c,
0xb05f31a8,0xb1a13000,0xb05f8000,0xb1a13000,0x2d55286a,0xaa9230b4,0x2d55286a,0xaa9230b4,0x316ab13a,0x30fdac54,0x316ab13a,0x30fdac54,0xa470ae49,0x2f2db18c,0xa470ae49,0x2f2db18c,
0xb0fd31a8,0x2a92b000,0xb0fd8000,0x2a92b000,0xa4702e49,0xaf2d286a,0xa4702e49,0xaf2d286a,0x305fac54,0xb1a1313a,0x305fac54,0xb1a1313a,0x316ab18c,0xad5530b4,0x316ab18c,0xad5530b4,
0xb16a31a8,0x30fdb000,0xb16a8000,0x30fdb000,0xaf2d30b4,0x31a1b18c,0xaf2d30b4,0x31a1b18c,0xa4702c54,0x305fb13a,0xa4702c54,0x305fb13a,0x2d55a86a,0x2a92ae49,0x2d55a86a,0x2a92ae49,
0xb1a131a8,0xaf2d3000,0xb1a18000,0xaf2d3000,0xb16a318c,0xad552e49,0xb16a318c,0xad552e49,0xb0fd313a,0xaa922c54,0xb0fd313a,0xaa922c54,0xb05f30b4,0xa470286a,0xb05f30b4,0xa470286a,
0x24700000,0x305f3000,0xa47031a8,0xb05fb000,0x2a92286a,0x30fd30b4,0xaa92a86a,0xb0fdb0b4,0x2d552c54,0x316a313a,0xad55ac54,0xb16ab13a,0x2f2d2e49,0x31a1318c,0xaf2dae49,0xb1a1b18c,
0x2a920000,0x2d553000,0xaa92b1a8,0xad55b000,0x305f2e49,0xa470286a,0xb05fae49,0x2470a86a,0x31a1313a,0xaf2dac54,0xb1a1b13a,0x2f2d2c54,0x30fd318c,0xb16ab0b4,0xb0fdb18c,0x316a30b4,
0x2d550000,0xb16ab000,0xad5531a8,0x316a3000,0x31a130b4,0xb05fb18c,0xb1a1b0b4,0x305f318c,0x2f2d313a,0x2470ac54,0xaf2db13a,0xa4702c54,0xaa92286a,0x30fd2e49,0x2a92a86a,0xb0fdae49,
0x2f2d0000,0xa470b000,0xaf2db1a8,0x24703000,0x30fd318c,0x316a2e49,0xb0fdb18c,0xb16aae49,0xaa922c54,0x2d55313a,0x2a92ac54,0xad55b13a,0xb1a1b0b4,0xb05fa86a,0x31a130b4,0x305f286a,
0x305f0000,0x31a13000,0xb05f31a8,0xb1a1b000,0x2d55318c,0xaa922e49,0xad55b18c,0x2a92ae49,0xb16aac54,0xb0fdb13a,0x316a2c54,0x30fd313a,0xa470b0b4,0x2f2da86a,0x247030b4,0xaf2d286a,
0x30fd0000,0xaa923000,0xb0fdb1a8,0x2a92b000,0xa47030b4,0xaf2db18c,0x2470b0b4,0x2f2d318c,0xb05fb13a,0x31a12c54,0x305f313a,0xb1a1ac54,0x316a286a,0xad552e49,0xb16aa86a,0x2d55ae49,
0x316a0000,0xb0fdb000,0xb16a31a8,0x30fd3000,0xaf2d2e49,0x31a1286a,0x2f2dae49,0xb1a1a86a,0x2470b13a,0xb05f2c54,0xa470313a,0x305fac54,0x2d55318c,0x2a92b0b4,0xad55b18c,0xaa9230b4,
0x31a10000,0x2f2db000,0xb1a1b1a8,0xaf2d3000,0xb16a286a,0xad5530b4,0x316aa86a,0x2d55b0b4,0x30fdac54,0x2a92b13a,0xb0fd2c54,0xaa92313a,0xb05f2e49,0xa470318c,0x305fae49,0x2470b18c,
0x31a10000,0x2f2d3000,0xb1a131a8,0xaf2db000,0xb16aa86a,0xad55b0b4,0x316a286a,0x2d5530b4,0x30fd2c54,0x2a92313a,0xb0fdac54,0xaa92b13a,0xb05fae49,0xa470b18c,0x305f2e49,0x2470318c,
0x316a0000,0xb0fd3000,0xb16ab1a8,0x30fdb000,0xaf2dae49,0x31a1a86a,0x2f2d2e49,0xb1a1286a,0x2470313a,0xb05fac54,0xa470b13a,0x305f2c54,0x2d55b18c,0x2a9230b4,0xad55318c,0xaa92b0b4,
0x30fd0000,0xaa92b000,0xb0fd31a8,0x2a923000,0xa470b0b4,0xaf2d318c,0x247030b4,0x2f2db18c,0xb05f313a,0x31a1ac54,0x305fb13a,0xb1a12c54,0x316aa86a,0xad55ae49,0xb16a286a,0x2d552e49,
0x305f0000,0x31a1b000,0xb05fb1a8,0xb1a13000,0x2d55b18c,0xaa92ae49,0xad55318c,0x2a922e49,0xb16a2c54,0xb0fd313a,0x316aac54,0x30fdb13a,0xa47030b4,0x2f2d286a,0x2470b0b4,0xaf2da86a,
0x2f2d0000,0xa4703000,0xaf2d31a8,0x2470b000,0x30fdb18c,0x316aae49,0xb0fd318c,0xb16a2e49,0xaa92ac54,0x2d55b13a,0x2a922c54,0xad55313a,0xb1a130b4,0xb05f286a,0x31a1b0b4,0x305fa86a,
0x2d550000,0xb16a3000,0xad55b1a8,0x316ab000,0x31a1b0b4,0xb05f318c,0xb1a130b4,0x305fb18c,0x2f2db13a,0x24702c54,0xaf2d313a,0xa470ac54,0xaa92a86a,0x30fdae49,0x2a92286a,0xb0fd2e49,
0x2a920000,0x2d55b000,0xaa9231a8,0xad553000,0x305fae49,0xa470a86a,0xb05f2e49,0x2470286a,0x31a1b13a,0xaf2d2c54,0xb1a1313a,0x2f2dac54,0x30fdb18c,0xb16a30b4,0xb0fd318c,0x316ab0b4,
0x24700000,0x305fb000,0xa470b1a8,0xb05f3000,0x2a92a86a,0x30fdb0b4,0xaa92286a,0xb0fd30b4,0x2d55ac54,0x316ab13a,0xad552c54,0xb16a313a,0x2f2dae49,0x31a1b18c,0xaf2d2e49,0xb1a1318c,
0x31a131a8,0xa47031a8,0x316a318c,0x2a92b18c,0x30fd313a,0xad55313a,0x305f30b4,0x2f2db0b4,0x2f2d3000,0xb05f3000,0x2d552e49,0x30fdae49,0x2a922c54,0xb16a2c54,0x2470286a,0x31a1a86a,
0x316a31a8,0xaa9231a8,0x2f2d30b4,0x305fb0b4,0x24702c54,0xb1a12c54,0xad55a86a,0x30fd286a,0xb0fdb000,0xad55b000,0xb1a1b18c,0xa470318c,0xb05fb13a,0x2f2db13a,0xaa92ae49,0xb16a2e49,
0x30fd31a8,0xad5531a8,0x24702e49,0x31a1ae49,0xb05fac54,0xaf2dac54,0xb16ab18c,0xaa92318c,0xaa92b000,0x316ab000,0x2f2d286a,0xb05fa86a,0x31a1313a,0xa470313a,0x2d5530b4,0x30fdb0b4,
0x305f31a8,0xaf2d31a8,0xad55286a,0x30fda86a,0xb16ab13a,0x2a92b13a,0x2470ae49,0xb1a12e49,0x31a13000,0x24703000,0x2a9230b4,0x316ab0b4,0xb0fdac54,0xad55ac54,0xaf2db18c,0xb05f318c,
0x2f2d31a8,0xb05f31a8,0xb0fda86a,0x2d55286a,0xaa92b13a,0x316ab13a,0x31a12e49,0xa470ae49,0xa4703000,0xb1a13000,0xb16ab0b4,0xaa9230b4,0x2d55ac54,0x30fdac54,0x305f318c,0x2f2db18c,
0x2d5531a8,0xb0fd31a8,0xb1a1ae49,0xa4702e49,0x2f2dac54,0x305fac54,0x2a92318c,0x316ab18c,0xb16ab000,0x2a92b000,0x305fa86a,0xaf2d286a,0x2470313a,0xb1a1313a,0xb0fdb0b4,0xad5530b4,
0x2a9231a8,0xb16a31a8,0xb05fb0b4,0xaf2d30b4,0x31a12c54,0xa4702c54,0xb0fd286a,0x2d55a86a,0x2d55b000,0x30fdb000,0x2470318c,0x31a1b18c,0xaf2db13a,0x305fb13a,0x316a2e49,0x2a92ae49,
0x247031a8,0xb1a131a8,0xaa92b18c,0xb16a318c,0x2d55313a,0xb0fd313a,0xaf2db0b4,0xb05f30b4,0x305f3000,0xaf2d3000,0xb0fdae49,0xad552e49,0x316a2c54,0xaa922c54,0xb1a1a86a,0xa470286a,
0xa4700000,0xb1a18000,0xaa92a86a,0x316a286a,0xad55ac54,0xb0fdac54,0xaf2dae49,0x305f2e49,0xb05fb000,0xaf2db000,0xb0fdb0b4,0x2d5530b4,0xb16ab13a,0xaa92b13a,0xb1a1b18c,0x2470318c,
0x2a928000,0x316a8000,0x305f2e49,0xaf2dae49,0x31a1313a,0x2470313a,0x30fd318c,0x2d55b18c,0x2d553000,0xb0fd3000,0xa470286a,0x31a1a86a,0xaf2dac54,0xb05fac54,0xb16ab0b4,0x2a9230b4,
0xad550000,0xb0fd8000,0xb1a1b0b4,0x247030b4,0xaf2db13a,0x305fb13a,0x2a92a86a,0xb16a286a,0x316a3000,0x2a923000,0x305f318c,0x2f2db18c,0xa4702c54,0xb1a12c54,0xb0fdae49,0x2d552e49,
0x2f2d8000,0x305f8000,0x30fd318c,0x2d55b18c,0xaa922c54,0xb16a2c54,0xb1a1b0b4,0xa47030b4,0xa470b000,0x31a1b000,0x316a2e49,0xaa92ae49,0x2d55313a,0xb0fd313a,0xb05fa86a,0x2f2d286a,
0xb05f0000,0xaf2d8000,0xad55b18c,0xb0fd318c,0x316a2c54,0x2a922c54,0x247030b4,0x31a1b0b4,0xb1a1b000,0x2470b000,0x2a92ae49,0xb16a2e49,0x30fd313a,0xad55313a,0xaf2d286a,0x305fa86a,
0x30fd8000,0x2d558000,0xa47030b4,0x31a1b0b4,0xb05fb13a,0x2f2db13a,0x316a286a,0xaa92a86a,0xaa923000,0xb16a3000,0xaf2db18c,0xb05f318c,0x31a12c54,0x24702c54,0xad552e49,0x30fdae49,
0xb16a8000,0xaa928000,0x2f2dae49,0xb05f2e49,0xa470313a,0xb1a1313a,0xad55b18c,0xb0fd318c,0x30fd3000,0xad553000,0xb1a1a86a,0x2470286a,0x305fac54,0x2f2dac54,0xaa9230b4,0x316ab0b4,
0x31a18000,0x24708000,0xb16a286a,0x2a92a86a,0x30fdac54,0x2d55ac54,0xb05f2e49,0x2f2dae49,0x2f2db000,0x305fb000,0xad5530b4,0x30fdb0b4,0x2a92b13a,0x316ab13a,0xa470318c,0x31a1b18c,
0x24700000,0x31a10000,0x2a92286a,0xb16aa86a,0x2d552c54,0x30fd2c54,0x2f2d2e49,0xb05fae49,0x305f3000,0x2f2d3000,0x30fd30b4,0xad55b0b4,0x316a313a,0x2a92313a,0x31a1318c,0xa470b18c,
0x2a920000,0x316a0000,0x305f2e49,0xaf2dae49,0x31a1313a,0x2470313a,0x30fd318c,0x2d55b18c,0x2d553000,0xb0fd3000,0xa470286a,0x31a1a86a,0xaf2dac54,0xb05fac54,0xb16ab0b4,0x2a9230b4,
0x2d550000,0x30fd0000,0x31a130b4,0xa470b0b4,0x2f2d313a,0xb05f313a,0xaa92286a,0x316aa86a,0xb16ab000,0xaa92b000,0xb05fb18c,0xaf2d318c,0x2470ac54,0x31a1ac54,0x30fd2e49,0xad55ae49,
0x2f2d0000,0x305f0000,0x30fd318c,0x2d55b18c,0xaa922c54,0xb16a2c54,0xb1a1b0b4,0xa47030b4,0xa470b000,0x31a1b000,0x316a2e49,0xaa92ae49,0x2d55313a,0xb0fd313a,0xb05fa86a,0x2f2d286a,
0x305f0000,0x2f2d0000,0x2d55318c,0x30fdb18c,0xb16aac54,0xaa92ac54,0xa470b0b4,0xb1a130b4,0x31a13000,0xa4703000,0xaa922e49,0x316aae49,0xb0fdb13a,0x2d55b13a,0x2f2da86a,0xb05f286a,
0x30fd0000,0x2d550000,0xa47030b4,0x31a1b0b4,0xb05fb13a,0x2f2db13a,0x316a286a,0xaa92a86a,0xaa923000,0xb16a3000,0xaf2db18c,0xb05f318c,0x31a12c54,0x24702c54,0xad552e49,0x30fdae49,
0x316a0000,0x2a920000,0xaf2d2e49,0x305fae49,0x2470b13a,0x31a1b13a,0x2d55318c,0x30fdb18c,0xb0fdb000,0x2d55b000,0x31a1286a,0xa470a86a,0xb05f2c54,0xaf2d2c54,0x2a92b0b4,0xb16a30b4,
0x31a10000,0x24700000,0xb16a286a,0x2a92a86a,0x30fdac54,0x2d55ac54,0xb05f2e49,0x2f2dae49,0x2f2db000,0x305fb000,0xad5530b4,0x30fdb0b4,0x2a92b13a,0x316ab13a,0xa470318c,0x31a1b18c,
0x31a131a8,0xa47031a8,0x316a318c,0x2a92b18c,0x30fd313a,0xad55313a,0x305f30b4,0x2f2db0b4,0x2f2d3000,0xb05f3000,0x2d552e49,0x30fdae49,0x2a922c54,0xb16a2c54,0x2470286a,0x31a1a86a,
0xb16ab1a8,0x2a92b1a8,0xaf2db0b4,0xb05f30b4,0xa470ac54,0x31a1ac54,0x2d55286a,0xb0fda86a,0x30fd3000,0x2d553000,0x31a1318c,0x2470b18c,0x305f313a,0xaf2d313a,0x2a922e49,0x316aae49,
0x30fd31a8,0xad5531a8,0x24702e49,0x31a1ae49,0xb05fac54,0xaf2dac54,0xb16ab18c,0xaa92318c,0xaa92b000,0x316ab000,0x2f2d286a,0xb05fa86a,0x31a1313a,0xa470313a,0x2d5530b4,0x30fdb0b4,
0xb05fb1a8,0x2f2db1a8,0x2d55a86a,0xb0fd286a,0x316a313a,0xaa92313a,0xa4702e49,0x31a1ae49,0xb1a1b000,0xa470b000,0xaa92b0b4,0xb16a30b4,0x30fd2c54,0x2d552c54,0x2f2d318c,0x305fb18c,
0x2f2d31a8,0xb05f31a8,0xb0fda86a,0x2d55286a,0xaa92b13a,0x316ab13a,0x31a12e49,0xa470ae49,0xa4703000,0xb1a13000,0xb16ab0b4,0xaa9230b4,0x2d55ac54,0x30fdac54,0x305f318c,0x2f2db18c,
0xad55b1a8,0x30fdb1a8,0x31a12e49,0x2470ae49,0xaf2d2c54,0xb05f2c54,0xaa92b18c,0xb16a318c,0x316a3000,0xaa923000,0xb05f286a,0x2f2da86a,0xa470b13a,0x31a1b13a,0x30fd30b4,0x2d55b0b4,
0x2a9231a8,0xb16a31a8,0xb05fb0b4,0xaf2d30b4,0x31a12c54,0xa4702c54,0xb0fd286a,0x2d55a86a,0x2d55b000,0x30fdb000,0x2470318c,0x31a1b18c,0xaf2db13a,0x305fb13a,0x316a2e49,0x2a92ae49,
0xa470b1a8,0x31a1b1a8,0x2a92318c,0x316ab18c,0xad55b13a,0x30fdb13a,0x2f2d30b4,0x305fb0b4,0xb05fb000,0x2f2db000,0x30fd2e49,0x2d55ae49,0xb16aac54,0x2a92ac54,0x31a1286a,0x2470a86a,
0x3beb3bfe,0x30992a48,0x3bf73bfe,0x2e142a48,0x3b8f3bc6,0x35403396,0x3bdc3bec,0x31f43080,0x3aed3b46,0x380236aa,0x3bb13bc9,0x34693365,0x3a0b3a83,0x393e38a6,0x3b743b95,0x35ce351d,
0x3bed3bfe,0x30672a48,0x3bf83bfe,0x2db02a48,0x3b9b3bcb,0x34f93334,0x3be33bef,0x3160301d,0x3b0b3b5a,0x3796364e,0x3bc13bd4,0x33df32a1,0x3a433aae,0x38fb3867,0x3b933bab,0x3529348d,
0x3bee3bfe,0x30362a48,0x3bf93bfe,0x2d4c2a48,0x3ba63bd1,0x34b132d2,0x3be93bf2,0x30cb2f72,0x3b283b6e,0x372635f1,0x3bd03bdd,0x32ea31db,0x3a783ad6,0x38b53828,0x3bad3bc0,0x348133f7,
0x3bf03bfe,0x30042a48,0x3bfa3bfe,0x2ce72a48,0x3bb13bd6,0x3469326f,0x3bee3bf5,0x30362eaa,0x3b433b80,0x36b53593,0x3bdc3be6,0x31f43115,0x3aaa3afc,0x386d37cd,0x3bc43bd1,0x33ae32d2,
0x3bf13bfe,0x2fa42a48,0x3bfb3bfe,0x2c832a48,0x3bbb3bdb,0x3420320d,0x3bf33bf7,0x2f402de2,0x3b5d3b91,0x36423534,0x3be73bed,0x30fd304e,0x3ad93b20,0x38223748,0x3bd73be0,0x325731aa,
0x3bf33bfe,0x2f402a48,0x3bfc3bfe,0x2c1f2a48,0x3bc43be0,0x33ae31aa,0x3bf73bf9,0x2e142d1a,0x3b743ba0,0x35ce34d5,0x3bf03bf4,0x30042f0e,0x3b053b41,0x37ac36c1,0x3be73bec,0x30fd3080,
0x3bf43bfe,0x2edc2a48,0x3bfd3bfe,0x2b752a48,0x3bcd3be4,0x331b3147,0x3bfa3bfb,0x2ce72c51,0x3b8a3baf,0x35583475,0x3bf73bf8,0x2e142d7e,0x3b2e3b5f,0x37103637,0x3bf33bf5,0x2f402eaa,
0x3bf63bfe,0x2e782a48,0x3bfd3bfe,0x2aac2a48,0x3bd53be8,0x328830e4,0x3bfd3bfd,0x2b752b11,0x3b9e3bbc,0x34e13414,0x3bfc3bfc,0x2c1f2bd9,0x3b533b7b,0x367035ab,0x3bfb3bfb,0x2c832c51,
0x38f13984,0x3a4b39cb,0x3b283b50,0x3726367c,0x37533852,0x3b1d3abc,0x3acc3afc,0x383837cd,0x348135f1,0x3bad3b6e,0x3a623a99,0x38d33887,0x2e14320d,0x3bf73bdb,0x39e93a27,0x3964391d,
0x394839cb,0x3a023984,0x3b583b77,0x365935c2,0x382238ba,0x3ad93a74,0x3b113b36,0x378036ee,0x35b63705,0x3b793b30,0x3abf3ae9,0x384d3807,0x31f4345d,0x3bdc3bb2,0x3a623a92,0x38d33891,
0x399b3a0f,0x39b5393a,0x3b823b99,0x35873505,0x3896391d,0x3a8e3a27,0x3b4e3b69,0x36873608,0x36e33807,0x3b393ae9,0x3b113b30,0x37803705,0x346935ab,0x3bb13b7b,0x3acc3af0,0x383837f9,
0x39e93a4f,0x396438ec,0x3ba63bb6,0x34b13444,0x3905397b,0x3a3b39d4,0x3b823b95,0x3587351d,0x38023887,0x3aed3a99,0x3b583b6e,0x365935f1,0x35ce36ee,0x3b743b36,0x3b283b41,0x372636c1,
0x3a333a8a,0x390e389b,0x3bc43bce,0x33ae3303,0x396d39d4,0x39e1397b,0x3bad3bb9,0x3481342c,0x388c3900,0x3a953a3f,0x3b933ba0,0x352934d5,0x37263812,0x3b283ae3,0x3b743b84,0x35ce357c,
0x3a783ac2,0x38b53848,0x3bdc3be2,0x31f43179,0x39d03a27,0x3980391d,0x3bd03bd6,0x32ea326f,0x390e3972,0x3a3339dc,0x3bc13bc9,0x33df3365,0x383838a6,0x3acc3a83,0x3bb13bb9,0x3469342c,
0x3ab83af6,0x385837e3,0x3bee3bf1,0x30362fd6,0x3a2b3a74,0x391838ba,0x3be93bec,0x30cb3080,0x398939dc,0x39c73972,0x3be33be6,0x31603115,0x38d33930,0x3a623a17,0x3bdc3be0,0x31f431aa,
0x3af33b25,0x37ee3732,0x3bfa3bfa,0x2ce72cb5,0x3a7f3abc,0x38ab3852,0x3bf93bf9,0x2d4c2d1a,0x39fa3a3f,0x39513900,0x3bf83bf8,0x2db02d7e,0x396439b1,0x39e9399f,0x3bf73bf7,0x2e142de2,
0xae140000,0x3bf73c00,0x396439a8,0x39e939a8,0xb481b20d,0x3bad3bdb,0x38d3391d,0x3a623a27,0xb753b5f1,0x3b1d3b6e,0x38383887,0x3acc3a99,0xb8f1b852,0x3a4b3abc,0x372637cd,0x3b283afc,
0x20b62e46,0x3c003bf6,0x39fa3a2f,0x39513913,0xb160ad1a,0x3be33bf9,0x398939c3,0x39c7398d,0xb570b414,0x3b863bbc,0x390e394d,0x3a3339fe,0xb802b6c1,0x3aed3b41,0x388c38ce,0x3a953a65,
0x2f40323e,0x3bf33bd9,0x3a7f3aa7,0x38ab3872,0xaaac27da,0x3bfd3bff,0x3a2b3a56,0x391838e2,0xb2eab04e,0x3bd03bed,0x39d039fe,0x3980394d,0xb5fdb4bd,0x3b6b3ba4,0x396d399f,0x39e139b1,
0x32ea34a5,0x3bd03ba8,0x3af33b0e,0x37ee378b,0x2c1f3080,0x3bfc3bec,0x3ab83ad6,0x38583828,0xadb0a248,0x3bf83c00,0x3a783a99,0x38b53887,0xb3aeb147,0x3bc43be4,0x3a333a56,0x390e38e2,
0x3511361f,0x3b973b64,0x3b533b64,0x3670361f,0x31c333f7,0x3bdf3bc0,0x3b2e3b41,0x371036c1,0x291b2f0e,0x3bfe3bf4,0x3b053b1a,0x37ac375e,0xae78a7da,0x3bf63bff,0x3ad93af0,0x382237f9,
0x369e378b,0x3b493b0e,0x3b9e3ba8,0x34e134a5,0x34b135ab,0x3ba63b7b,0x3b8a3b95,0x3558351d,0x31603365,0x3be33bc9,0x3b743b80,0x35ce3593,0x291b2eaa,0x3bfe3bf5,0x3b5d3b69,0x36423608,
0x380d3872,0x3ae63aa7,0x3bd53bd9,0x3288323e,0x36703748,0x3b533b20,0x3bcd3bd1,0x331b32d2,0x34b13593,0x3ba63b80,0x3bc43bc9,0x33ae3365,0x31c33396,0x3bdf3bc6,0x3bbb3bc0,0x342033f7,
0x38bf3913,0x3a713a2f,0x3bf63bf6,0x2e782e46,0x380d3867,0x3ae63aae,0x3bf43bf5,0x2edc2eaa,0x369e375e,0x3b493b1a,0x3bf33bf4,0x2f402f0e,0x351135da,0x3b973b72,0x3bf13bf2,0x2fa42f72,
0xba0bb984,0x393e39cb,0x35ce367c,0x3b743b50,0xbaedba83,0x380238a6,0x3469351d,0x3bb13b95,0xbb8fbb46,0x354036aa,0x31f43365,0x3bdc3bc9,0xbbebbbc6,0x30993396,0x2e143080,0x3bf73bec,
0xb92bb89b,0x3a1b3a8a,0x38023848,0x3aed3ac2,0xba2bb9b1,0x3918399f,0x36e33775,0x3b393b14,0xbaf9ba99,0x37d83887,0x35b6364e,0x3b793b5a,0xbb8fbb4b,0x35403693,0x3481351d,0x3bad3b95,
0xb82db732,0x3ad33b25,0x3905393a,0x3a3b3a0f,0xb93eb8ba,0x3a0b3a74,0x389638ce,0x3a8e3a65,0xba2bb9ba,0x39183996,0x3822385d,0x3ad93ab5,0xbaedba92,0x38023891,0x375337cd,0x3b1d3afc,
0xb62bb505,0x3b623b99,0x39e93a0f,0x3964393a,0xb82db748,0x3ad33b20,0x399b39c3,0x39b5398d,0xb92bb8b0,0x3a1b3a7c,0x39483972,0x3a0239dc,0xba0bb99f,0x393e39b1,0x38f1391d,0x3a4b3a27,
0xb3aeb179,0x3bc43be2,0x3aaa3ac2,0x386d3848,0xb5fdb4ed,0x3b6b3b9d,0x3a783a92,0x38b53891,0xb802b705,0x3aed3b30,0x3a433a5e,0x38fb38d8,0xb8f1b87c,0x3a4b3aa0,0x3a0b3a27,0x393e391d,
0xadb0a648,0x3bf83bff,0x3b433b50,0x36b5367c,0xb2eab0e4,0x3bd03be8,0x3b283b36,0x372636ee,0xb570b475,0x3b863baf,0x3b0b3b1a,0x3796375e,0xb753b665,0x3b1d3b55,0x3aed3afc,0x380237cd,
0x2c1f2fd6,0x3bfc3bf1,0x3bb13bb6,0x34693444,0xaaac1e48,0x3bfd3c00,0x3ba63bab,0x34b1348d,0xb160af0e,0x3be33bf4,0x3b9b3ba0,0x34f934d5,0xb481b334,0x3bad3bcb,0x3b8f3b95,0x3540351d,
0x32ea3444,0x3bd03bb6,0x3bf03bf1,0x30042fd6,0x2f403147,0x3bf33be4,0x3bee3bef,0x3036301d,0x20b62bd9,0x3c003bfc,0x3bed3bed,0x3067304e,0xae14a97f,0x3bf73bfe,0x3beb3bec,0x30993080,
0x3be93bfe,0x30cb2a48,0x3bd73bfe,0x32572a48,0x3b823bc0,0x358733f7,0x3b053b84,0x37ac357c,0x3acc3b30,0x38383705,0x39923a5e,0x39be38d8,0x39d03a56,0x398038e2,0x373d38a6,0x3b223a83,
0x3be73bfe,0x30fd2a48,0x3bd53bfe,0x32882a48,0x3b743bb9,0x35ce342c,0x3af33b7b,0x37ee35ab,0x3aaa3b1a,0x386d375e,0x39643a3f,0x39e93900,0x39923a27,0x39be391d,0x369e3867,0x3b493aae,
0x3be53bfe,0x312e2a48,0x3bd23bfe,0x32b92a48,0x3b673bb2,0x3614345d,0x3ae03b72,0x381735da,0x3a873b02,0x38a037b7,0x39353a1f,0x3a133927,0x395139f6,0x39fa3956,0x35fd3828,0x3b6b3ad6,
0x3be33bfe,0x31602a48,0x3bd03bfe,0x32ea2a48,0x3b583bab,0x3659348d,0x3acc3b69,0x38383608,0x3a623ae9,0x38d33807,0x390539fe,0x3a3b394d,0x390e39c3,0x3a33398d,0x355837cd,0x3b8a3afc,
0x3be13bfe,0x31912a48,0x3bcd3bfe,0x331b2a48,0x3b493ba4,0x369e34bd,0x3ab83b5f,0x38583637,0x3a3b3ad0,0x39053832,0x38d339dc,0x3a623972,0x38c9398d,0x3a6939c3,0x34b13748,0x3ba63b20,
0x3bdf3bfe,0x31c32a48,0x3bca3bfe,0x334c2a48,0x3b393b9d,0x36e334ed,0x3aa33b55,0x38773665,0x3a133ab5,0x3935385d,0x38a039ba,0x3a873996,0x38813956,0x3a9c39f6,0x340836c1,0x3bbe3b41,
0x3bdc3bfe,0x31f42a48,0x3bc73bfe,0x337d2a48,0x3b283b95,0x3726351d,0x3a8e3b4b,0x38963693,0x39e93a99,0x39643887,0x386d3996,0x3aaa39ba,0x3838391d,0x3acc3a27,0x32b93637,0x3bd23b5f,
0x3bda3bfe,0x32262a48,0x3bc43bfe,0x33ae2a48,0x3b173b8c,0x376a354c,0x3a783b41,0x38b536c1,0x39be3a7c,0x399238b0,0x38383972,0x3acc39dc,0x37d838e2,0x3af93a56,0x316035ab,0x3be33b7b,
0x3896393a,0x3a8e3a0f,0x31603505,0x3be33b99,0x365937cd,0x3b583afc,0xb03624b6,0x3bee3c00,0x328834d5,0x3bd53ba0,0xb6b5b475,0x3b433baf,0x1a482eaa,0x3c003bf5,0xb95bb867,0x39f23aae,
0x383838ec,0x3acc3a4f,0x2f403444,0x3bf33bb6,0x355836ee,0x3b8a3b36,0xb257a97f,0x3bd73bfe,0x30043365,0x3bf03bc9,0xb7d8b593,0x3af93b80,0xadb024b6,0x3bf83c00,0xb9e1b8f6,0x396d3a47,
0x37ac389b,0x3b053a8a,0x2b753303,0x3bfd3bce,0x34513608,0x3bb43b69,0xb438aeaa,0x3bb73bf5,0x29e33115,0x3bfe3be6,0xb877b6aa,0x3aa33b46,0xb1c3ac51,0x3bdf3bfb,0xba5ab97b,0x38dd39d4,
0x36e33848,0x3b393ac2,0x1a483179,0x3c003be2,0x3288351d,0x3bd53b95,0xb540b147,0x3b8f3be4,0xa8522d7e,0x3bff3bf8,0xb8fbb7b7,0x3a433b02,0xb451b0e4,0x3bb43be8,0xbac6b9f6,0x38423956,
0x361437e3,0x3b673af6,0xaaac2fd6,0x3bfd3bf1,0x3067342c,0x3bed3bb9,0xb642b334,0x3b5d3bcb,0xaf402248,0x3bf33c00,0xb976b85d,0x39d83ab5,0xb5b6b396,0x3b793bc6,0xbb22ba65,0x373d38ce,
0x35403732,0x3b8f3b25,0xaedc2cb5,0x3bf43bfa,0x2c83326f,0x3bfb3bd6,0xb73db48d,0x3b223bab,0xb226abd9,0x3bda3bfc,0xb9e9b8d8,0x39643a5e,0xb710b51d,0x3b2e3b95,0xbb70bac9,0x35e5383d,
0x3469367c,0x3bb13b50,0xb12e2648,0x3be53bff,0x1a483080,0x3c003bec,0xb817b57c,0x3ae03b84,0xb451b04e,0x3bb43bed,0xba52b94d,0x38e739fe,0xb82db665,0x3ad33b55,0xbbadbb20,0x34813748,
0x331b35c2,0x3bcd3b77,0xb2eaa648,0x3bd03bff,0xac1f2d1a,0x3bfc3bf9,0xb88cb665,0x3a953b55,0xb587b2a1,0x3b823bd4,0xbab1b9ba,0x38623996,0xb8c9b7a1,0x3a693b08,0xbbdabb69,0x32263608,
0xb257ae46,0x3bd73bf6,0xbae0ba2f,0x38173913,0xb642b4bd,0x3b5d3ba4,0xbbc7bb69,0x337d3608,0xb88cb7b7,0x3a953b02,0xbbfcbbf8,0xac1f2d7e,0xb9c7b930,0x39893a17,0xbb79bbd1,0xb5b6b2d2,
0xb4c9b23e,0x3ba23bd9,0xbb43baa7,0x36b53872,0xb7eeb665,0x3af33b55,0xbbf1bbb2,0x2fa4345d,0xb95bb8b0,0x39f23a7c,0xbbdabbff,0xb226a8b6,0xba7fb9f6,0x38ab3956,0xbaffbb84,0xb7c2b57c,
0xb659b4a5,0x3b583ba8,0xbb93bb0e,0x3529378b,0xb8bfb7f9,0x3a713af0,0xbc00bbe4,0x1a483147,0xba13b972,0x393539dc,0xbb97bbe6,0xb511b115,0xbb17baa0,0x376a387c,0xba62bb14,0xb8d3b775,
0xb7d8b61f,0x3af93b64,0xbbcdbb64,0x331b361f,0xb976b8ba,0x39d83a74,0xbbf3bbfd,0xaf402b11,0xbab1ba1f,0x38623927,0xbb33bbaf,0xb6f9b475,0xbb8abb2b,0x3558371b,0xb9a4ba83,0xb9adb8a6,
0xb8a0b78b,0x3a873b0e,0xbbf1bba8,0x2fa434a5,0xba1bb969,0x392b39e5,0xbbcabbfd,0xb34cab11,0xbb33bab5,0x36f9385d,0xbab1bb5a,0xb862b64e,0xbbd7bb95,0x3257351d,0xb8c9b9d4,0xba69b97b,
0xb948b872,0x3a023aa7,0xbc00bbd9,0x23db323e,0xbaaaba07,0x386d3943,0xbb86bbe4,0xb570b147,0xbb97bb30,0x35113705,0xba13bae9,0xb935b807,0xbbfdbbdb,0x2b75320d,0xb7acb909,0xbb05ba37,
0xb9e1b913,0x396d3a2f,0xbbf8bbf6,0xadb02e46,0xbb22ba92,0x373d3891,0xbb28bbb2,0xb726b45d,0xbbdabb91,0x32263534,0xb95bba5e,0xb9f2b8d8,0xbbf9bbfd,0xad4c2b11,0xb59fb828,0xbb7dbad6,
0xba69b9a8,0x38c939a8,0xbbdabc00,0xb2268000,0xbb82bb08,0x358737a1,0xbab1bb69,0xb862b608,0xbbfcbbd4,0x2c1f32a1,0xb88cb9ba,0xba95b996,0xbbcdbbf9,0xb31bad1a,0xb2eab665,0xbbd0bb55,
0xbac6ba4f,0x384238ec,0xba4bbaf6,0xb8f1b7e3,0xbb7dbb2b,0x359f371b,0xb88cb97b,0xba95b9d4,0xbbe7bbbc,0x30fd3414,0xb4c9b705,0xbba2bb30,0xbbfebbfd,0xa9e32b11,0x9a48b0e4,0xbc00bbe8,
0xbb58baf6,0x365937e3,0xb976ba4f,0xb9d8b8ec,0xbbdabba4,0x322634bd,0xb6ccb87c,0xbb3ebaa0,0xbc00bbf8,0xa57f2d7e,0xb004b475,0xbbf0bbaf,0xbbc7bbef,0xb37db01d,0x31f427da,0xbbdcbbff,
0xbbbebb77,0x340835c2,0xb881b984,0xba9cb9cb,0xbbffbbec,0x27113080,0xb451b6c1,0xbbb4bb41,0xbbd7bbf8,0xb257ad7e,0x2aacaf0e,0xbbfdbbf4,0xbb49bb9d,0xb69eb4ed,0x35e532d2,0xbb70bbd1,
0xbbf6bbce,0x2e783303,0xb6e3b89b,0xbb39ba8a,0xbbedbc00,0xb067a4b6,0xaedcb45d,0xbbf4bbb2,0xbb70bbbc,0xb5e5b414,0x334c2bd9,0xbbcabbfc,0xba87bb08,0xb8a0b7a1,0x384d3637,0xbabfbb5f,
0xbbfdbbfa,0xaaac2cb5,0xb499b732,0xbbaabb25,0xbba2bbe0,0xb4c9b1aa,0x2b75af72,0xbbfdbbf2,0xbaccbb46,0xb838b6aa,0x36593365,0xbb58bbc9,0xb989ba37,0xb9c7b909,0x39803867,0xb9d0baae,
0xbbd5bbfa,0xb288acb5,0xb067b505,0xbbedbb99,0xbb22bb8c,0xb73db54c,0x331b297f,0xbbcdbbfe,0xb9f2ba99,0xb95bb887,0x386d364e,0xbaaabb5a,0xb858b930,0xbab8ba17,0x3a7f398d,0xb8abb9c3,
0xbb7dbbce,0xb59fb303,0x23dbb179,0xbc00bbe2,0xba71bb08,0xb8bfb7a1,0x3614326f,0xbb67bbd6,0xb8e7b9ba,0xba52b996,0x3989385d,0xb9c7bab5,0xb5fdb7f9,0xbb6bbaf0,0x3b433a83,0xb6b5b8a6,
0xbaf9bb77,0xb7d8b5c2,0x3160a648,0xbbe3bbff,0xb992ba56,0xb9beb8e2,0x383835ab,0xbaccbb7b,0xb76ab8b0,0xbb17ba7c,0x3a783972,0xb8b5b9dc,0xb226b54c,0xbbdabb8c,0x3bc43b41,0xb3aeb6c1,
0x3bd93bf6,0xb23eae46,0x38ec393a,0xba4fba0f,0x3b643ba8,0xb61fb4a5,0x3848389b,0xbac2ba8a,0x3aa73b0e,0xb872b78b,0x373237e3,0xbb25baf6,0x39a83a2f,0xb9a8b913,0x35c2367c,0xbb77bb50,
0x3bad3bda,0xb481b226,0x385838a0,0xbab8ba87,0x3b223b70,0xb73db5e5,0x3780380d,0xbb11bae6,0x3a5a3ac6,0xb8ddb842,0x364236e3,0xbb5dbb39,0x395b39e1,0xb9f2b96d,0x34f9359f,0xbb9bbb7d,
0x3b723bab,0xb5dab48d,0x377537f9,0xbb14baf0,0x3ad63b2b,0xb828b71b,0x366536ee,0xbb55bb36,0x3a073a74,0xb943b8ba,0x354c35da,0xbb8cbb72,0x3909398d,0xba37b9c3,0x342c34bd,0xbbb9bba4,
0x3b283b6b,0xb726b5fd,0x362b369e,0xbb62bb49,0x3a7f3ad9,0xb8abb822,0x354035b6,0xbb8fbb79,0x39ad3a1b,0xb9a4b92b,0x345134c9,0xbbb4bba2,0x38b53935,0xba78ba13,0x32b933ae,0xbbd2bbc4,
0x3ad03b1a,0xb832b75e,0x34d53534,0xbba0bb91,0x3a1f3a7c,0xb927b8b0,0x34143475,0xbbbcbbaf,0x394d39ba,0xb9feb996,0x32a13365,0xbbd4bbc9,0x385d38d8,0xbab5ba5e,0x311531db,0xbbe6bbdd,
0x3a693ab8,0xb8c9b858,0x32ea337d,0xbbd0bbc7,0x39b53a13,0xb99bb935,0x31c33257,0xbbdfbbd7,0x38e73951,0xba52b9fa,0x3099312e,0xbbebbbe5,0x38023877,0xbaedbaa3,0x2edc3004,0xbbf4bbf0,
0x39f63a47,0xb956b8f6,0x301d3080,0xbbefbbec,0x3943399f,0xba07b9b1,0x2eaa2f72,0xbbf5bbf2,0x387c38e2,0xbaa0ba56,0x2d1a2de2,0xbbf9bbf7,0x37483812,0xbb20bae3,0x2b112c51,0xbbfdbbfb,
0x397639c7,0xb9d8b989,0x291b29e3,0xbbfebbfe,0x38c93922,0xba69ba23,0x27112852,0xbbffbbff,0x380d386d,0xbae6baaa,0x23db257f,0xbc00bc00,0x36873753,0xbb4ebb1d,0x1a4820b6,0xbc00bc00,
0x38723913,0xbaa7ba2f,0x34443505,0xbbb6bb99,0x361f378b,0xbb64bb0e,0x31793303,0xbbe2bbce,0x323e34a5,0xbbd9bba8,0x2cb52fd6,0xbbfabbf1,0x2e46,0xbc00bbf6,0xa6482648,0xbbffbbff,
0x382d38c9,0xbad3ba69,0x334c3451,0xbbcabbb4,0x35b63710,0xbb79bb2e,0x309931f4,0xbbebbbdc,0x31c33451,0xbbdfbbb4,0x2b752e78,0xbbfdbbf6,0x9a482db0,0xbc00bbf8,0xa71123db,0xbbffbc00,
0x37cd387c,0xbafcbaa0,0x320d3334,0xbbdbbbcb,0x354c3693,0xbb8cbb4b,0x2f7230e4,0xbbf2bbe8,0x314733f7,0xbbe4bbc0,0x297f2d1a,0xbbfebbf9,0x9e482d1a,0xbc00bbf9,0xa7da1e48,0xbbffbc00,
0x373d382d,0xbb22bad3,0x30cb31c3,0xbbe9bbdf,0x34e13614,0xbb9ebb67,0x2db02fa4,0xbbf8bbf1,0x30cb334c,0xbbe9bbca,0x27112b75,0xbbffbbfd,0xa0b62c83,0xbc00bbfb,0xa8529a48,0xbbffbc00,
0x36aa37b7,0xbb46bb02,0x2f0e304e,0xbbf4bbed,0x34753593,0xbbafbb80,0x2bd92d7e,0xbbfcbbf8,0x304e32a1,0xbbedbbd4,0x224828b6,0xbc00bbff,0xa2482bd9,0xbc00bbfc,0xa8b6a248,0xbbffbc00,
0x36143710,0xbb67bb2e,0x2c832db0,0xbbfbbbf8,0x34083511,0xbbbebb97,0x28522aac,0xbbffbbfd,0x2fa431f4,0xbbf1bbdc,0x9a4823db,0xbc00bc00,0xa3db2aac,0xbc00bbfd,0xa91ba57f,0xbbfebc00,
0x357c3665,0xbb84bb55,0x27da297f,0xbbffbbfe,0x3334348d,0xbbcbbbab,0x1e4824b6,0xbc00bc00,0x2eaa3147,0xbbf5bbe4,0xa4b69e48,0xbc00bc00,0xa4b6297f,0xbc00bbfe,0xa97fa7da,0xbbfebbff,
0x34e135b6,0xbb9ebb79,0xa0b69a48,0xbc00bc00,0x32573408,0xbbd7bbbe,0xa57fa3db,0xbc00bc00,0x2db03099,0xbbf8bbeb,0xa852a711,0xbbffbbff,0xa57f2852,0xbc00bbff,0xa9e3a91b,0xbbfebbfe,
0x3bf63c00,0x2e460000,0x39cb3984,0xb984b9cb,0x3ba83bd9,0x34a5323e,0x3a4f3a0f,0xb8ecb93a,0x3b0e3b64,0x378b361f,0x3ac23a8a,0xb848b89b,0x3a2f3aa7,0x39133872,0x3b253af6,0xb732b7e3,
0x3c003bf6,0xa0b6ae78,0x392b38e7,0xba1bba52,0x3be13bf9,0x31912d4c,0x39ad396d,0xb9a4b9e1,0x3b7d3bb7,0x359f3438,0x3a2339e9,0xb922b964,0x3ad93b33,0x382236f9,0x3a8e3a5a,0xb896b8dd,
0x3bf23bd6,0xaf72b26f,0x387c383d,0xbaa0bac9,0x3bfd3bff,0x2b11a7da,0x38f638ba,0xba47ba74,0x3bcb3bec,0x33343080,0x39693930,0xb9e5ba17,0x3b5f3b9d,0x363734ed,0x39d4399f,0xb97bb9b1,
0x3bcd3ba2,0xb31bb4c9,0x37803710,0xbb11bb2e,0x3bfc3beb,0xac1fb099,0x382d37ee,0xbad3baf3,0x3bf73c00,0x2e1423db,0x38963862,0xba8ebab1,0x3bbe3be1,0x34083191,0x38fb38c9,0xba43ba69,
0x3b913b5a,0xb534b64e,0x35f13593,0xbb6ebb80,0x3bdd3bbc,0xb1dbb414,0x36aa364e,0xbb46bb5a,0x3bff3bf4,0xa8b6af0e,0x375e3705,0xbb1abb30,0x3bf43bff,0x2f0e28b6,0x380737b7,0xbae9bb02,
0x3b3e3aff,0xb6ccb7c2,0x34513408,0xbbb4bbbe,0x3ba23b74,0xb4c9b5ce,0x34e13499,0xbb9ebbaa,0x3be33bc7,0xb160b37d,0x35703529,0xbb86bb93,0x3bff3bf6,0xa852ae78,0x35fd35b6,0xbb6bbb79,
0x3ad63a92,0xb828b891,0x314730e4,0xbbe4bbe8,0x3b4b3b14,0xb693b775,0x320d31aa,0xbbdbbbe0,0x3ba43b7b,0xb4bdb5ab,0x32d2326f,0xbbd1bbd6,0x3be03bc6,0xb1aab396,0x33963334,0xbbc6bbcb,
0x3a5a3a13,0xb8ddb935,0x2b752aac,0xbbfdbbfd,0x3ad93a9c,0xb822b881,0x2c832c1f,0xbbfbbbfc,0x3b433b11,0xb6b5b780,0x2d4c2ce7,0xbbf9bbfa,0x3b973b70,0xb511b5e5,0x2e142db0,0xbbf7bbf8,
0x391339a8,0x3a2f39a8,0x3b773b50,0xb5c2b67c,0x378b3872,0x3b0e3aa7,0x3bb63b99,0xb444b505,0x34a5361f,0x3ba83b64,0x3be23bce,0xb179b303,0x2e46323e,0x3bf63bd9,0x3bfa3bf1,0xacb5afd6,
0x39fa3a71,0x395138bf,0x3aed3abf,0xb802b84d,0x38e73976,0x3a5239d8,0x3b3e3b17,0xb6ccb76a,0x3753384d,0x3b1d3abf,0x3b823b62,0xb587b62b,0x349935fd,0x3baa3b6b,0x3bb73b9e,0xb438b4e1,
0x3abc3b14,0x38523775,0x3a373a07,0xb909b943,0x39e53a56,0x396938e2,0x3a923a65,0xb891b8ce,0x38e23969,0x3a5639e5,0x3ae33abc,0xb812b852,0x37753852,0x3b143abc,0x3b2b3b08,0xb71bb7a1,
0x3b533b8f,0x36703540,0x395b392b,0xb9f2ba1b,0x3ab83b0b,0x38583796,0x39b53989,0xb99bb9c7,0x39f23a5a,0x395b38dd,0x3a0b39e1,0xb93eb96d,0x39053980,0x3a3b39d0,0x3a5a3a33,0xb8ddb90e,
0x3bbc3bdd,0x341431db,0x385d3832,0xbab5bad0,0x3b5a3b91,0x364e3534,0x38b03887,0xba7cba99,0x3ad03b1a,0x3832375e,0x390038d8,0xba3fba5e,0x3a1f3a7c,0x392738b0,0x394d3927,0xb9feba1f,
0x3bf63bff,0x2e782852,0x36873642,0xbb4ebb5d,0x3bc73be3,0x337d3160,0x371036cc,0xbb2ebb3e,0x3b743ba2,0x35ce34c9,0x37963753,0xbb0bbb1d,0x3aff3b3e,0x37c236cc,0x380d37d8,0xbae6baf9,
0x3bfd3bf2,0xab11af72,0x342c33f7,0xbbb9bbc0,0x3bfb3c00,0x2c511e48,0x348d345d,0xbbabbbb2,0x3bdb3bef,0x320d301d,0x34ed34bd,0xbb9dbba4,0x3b9d3bc0,0x34ed33f7,0x354c351d,0xbb8cbb95,
0x3bd23bb7,0xb2b9b438,0x2edc2e78,0xbbf4bbf6,0x3bf63be7,0xae78b0fd,0x2fa42f40,0xbbf1bbf3,0x3c003bfe,0x20b6a9e3,0x30363004,0xbbeebbf0,0x3bf13bfc,0x2fa42c1f,0x30993067,0xbbebbbed,
0x3bf43c00,0xaedc9a48,0x3a9539d0,0x388c3980,0x3b9b3bd2,0xb4f9b2b9,0x3ba63b33,0x34b136f9,0x3aed3b4e,0xb802b687,0x3c003beb,0xa0b63099,0x39f23a78,0xb95bb8b5,0x3b9b3be5,0xb4f9b12e,
0x3c003bf7,0xa4b62de2,0x3a273943,0x391d3a07,0x3bc63bef,0xb396b01d,0x3b723ae3,0x35da3812,0x3b2b3b84,0xb71bb57c,0x3bfd3bd1,0x2b1132d2,0x3a373abc,0xb909b852,0x3bb93bf5,0xb42caeaa,
0x3bfb3bdc,0x2c8331f4,0x39ad38ab,0x39a43a7f,0x3be53bfe,0xb12ea9e3,0x3b333a87,0x36f938a0,0x3b623bb1,0xb62bb469,0x3bf13bad,0x2fa43481,0x3a783af9,0xb8b5b7d8,0x3bd23bfe,0xb2b9a9e3,
0x3be63baf,0x31153475,0x39273807,0x3a1f3ae9,0x3bf83bff,0xad7e28b6,0x3ae93a1f,0x38073927,0x3b913bd4,0xb534b2a1,0x3bdd3b80,0x31db3593,0x3ab53b30,0xb85db705,0x3be63c00,0xb1152248,
0x3bc13b70,0x33df35e5,0x389636b5,0x3a8e3b43,0x3c003bf1,0xa0b62fa4,0x3a9539ad,0x388c39a4,0x3bb73bed,0xb438b067,0x3bc13b49,0x33df369e,0x3aed3b62,0xb802b62b,0x3bf43bfb,0xaedc2c83,
0x3b8c3b20,0x354c3748,0x37f9354c,0x3af03b8c,0x3bfb3bd6,0x2c51326f,0x3a373930,0x39093a17,0x3bd63bfb,0xb26fac51,0x3b9d3b08,0x34ed37a1,0x3b203b8c,0xb748b54c,0x3bfd3bef,0xab11301d,
0x3b493abf,0x369e384d,0x36b533ae,0x3b433bc4,0x3beb3bad,0x30993481,0x39d038ab,0x39803a7f,0x3bed3c00,0xb0671a48,0x3b703abf,0x35e5384d,0x3b4e3bb1,0xb687b469,0x3c003bdc,0x9a4831f4,
0x3af63a4f,0x37e338ec,0x356430b2,0x3b883bea,0x3bce3b77,0x330335c2,0x395f381d,0x39ed3add,0x3bfa3bfa,0xacb52cb5,0x3b3b3a6d,0x36d738c4,0x3b773bce,0xb5c2b303,0x3bfe3bc3,0x2a4833c6,
0x38b5395b,0xba78b9f2,0x3a7f3b22,0xb8abb73d,0x36873802,0xbb4ebaed,0x38c939b5,0xba69b99b,0x32b934f9,0xbbd2bb9b,0x35403780,0xbb8fbb11,0x1a482edc,0xbc00bbf4,0x271131c3,0xbbffbbdf,
0x38f6399f,0xba47b9b1,0x3aae3b4b,0xb867b693,0x36ee383d,0xbb36bac9,0x38f639e5,0xba47b969,0x3334354c,0xbbcbbb8c,0x357c37cd,0xbb84bafc,0x1e482f72,0xbc00bbf2,0x27da320d,0xbbffbbdb,
0x393539e1,0xba13b96d,0x3ad93b70,0xb822b5e5,0x37533877,0xbb1dbaa3,0x39223a13,0xba23b935,0x33ae359f,0xbbc4bb7d,0x35b6380d,0xbb79bae6,0x20b63004,0xbc00bbf0,0x28523257,0xbbffbbd7,
0x39723a1f,0xb9dcb927,0x3b023b91,0xb7b7b534,0x37b738b0,0xbb02ba7c,0x394d3a3f,0xb9feb900,0x341435f1,0xbbbcbb6e,0x35f13832,0xbb6ebad0,0x2248304e,0xbc00bbed,0x28b632a1,0xbbffbbd4,
0x39ad3a5a,0xb9a4b8dd,0x3b283bad,0xb726b481,0x380d38e7,0xbae6ba52,0x39763a69,0xb9d8b8c9,0x34513642,0xbbb4bb5d,0x362b3858,0xbb62bab8,0x23db3099,0xbc00bbeb,0x291b32ea,0xbbfebbd0,
0x39e53a92,0xb969b891,0x3b4b3bc6,0xb693b396,0x383d391d,0xbac9ba27,0x399f3a92,0xb9b1b891,0x348d3693,0xbbabbb4b,0x3665387c,0xbb55baa0,0x24b630e4,0xbc00bbe8,0x297f3334,0xbbfebbcb,
0x3a1b3ac6,0xb92bb842,0x3b6b3bda,0xb5fdb226,0x386d3951,0xbaaab9fa,0x39c73ab8,0xb989b858,0x34c936e3,0xbba2bb39,0x369e38a0,0xbb49ba87,0x257f312e,0xbc00bbe5,0x29e3337d,0xbbfebbc7,
0x3a4f3af6,0xb8ecb7e3,0x3b883bea,0xb564b0b2,0x389b3984,0xba8ab9cb,0x39ed3add,0xb95fb81d,0x35053732,0xbb99bb25,0x36d738c4,0xbb3bba6d,0x26483179,0xbbffbbe2,0x2a4833c6,0xbbfebbc3,
0x3bd53bf6,0x32882e78,0x37c238e7,0x3aff3a52,0x3b533b9e,0x367034e1,0x32573587,0x3bd73b82,0x3a7f3af3,0x38ab37ee,0xaedc29e3,0x3bf43bfe,0x396439fa,0x39e93951,0xb670b420,0x3b533bbb,
0x3b9d3bd6,0x34ed326f,0x3637383d,0x3b5f3ac9,0x3ae33b4b,0x38123693,0x2d1a3396,0x3bf93bc6,0x39d43a65,0x397b38ce,0xb396ad1a,0x3bc63bf9,0x387c3930,0x3aa03a17,0xb83db637,0x3ac93b5f,
0x3b4e3ba2,0x368734c9,0x34993710,0x3baa3b2e,0x3a5a3ae0,0x38dd3817,0xa91b3004,0x3bfe3bf0,0x390e39be,0x3a333992,0xb5ceb288,0x3b743bd5,0x36f9384d,0x3b333abf,0xb92bb817,0x3a1b3ae0,
0x3ae93b5a,0x3807364e,0x31db3593,0x3bdd3b80,0x39ba3a5e,0x399638d8,0xb1152248,0x3be63c00,0x38323900,0x3ad03a3f,0xb7b7b534,0x3b023b91,0x34d536aa,0x3ba03b46,0xb9feb900,0x394d3a3f,
0x3a713aff,0x38bf37c2,0x2ce73408,0x3bfa3bbe,0x390539c7,0x3a3b3989,0xb469ae78,0x3bb13bf6,0x3687382d,0x3b4e3ad3,0xb8bfb710,0x3a713b2e,0x312e3499,0x3be53baa,0xbab1b9d0,0x38623980,
0x39e53a92,0x39693891,0xa7da30e4,0x3bff3be8,0x383d391d,0x3ac93a27,0xb637b2d2,0x3b5f3bd1,0x348d3693,0x3bab3b4b,0xb98db867,0x39c33aae,0x24b630e4,0x3c003be8,0xbb41ba83,0x36c138a6,
0x39483a13,0x3a023935,0xb0672aac,0x3bed3bfd,0x36cc3862,0x3b3e3ab1,0xb7eeb529,0x3af33b93,0x30fd34b1,0x3be73ba6,0xba43b935,0x38fb3a13,0xb00423db,0x3bf03c00,0xbbaabb17,0x3499376a,
0x389b3984,0x3a8a39cb,0xb3c6aa48,0x3bc33bfe,0x35053732,0x3b993b25,0xb8c4b6d7,0x3a6d3b3b,0x26483179,0x3bff3be2,0xbaddb9ed,0x381d395f,0xb444afd6,0x3bb63bf1,0xbbeabb88,0x30b23564,
0x380d38bf,0x3ae63a71,0xb948b84d,0x3a023abf,0x3511369e,0x3b973b49,0xbad9ba23,0x38223922,0x2f4032ea,0x3bf33bd0,0xbbc7bb67,0x337d3614,0xae1420b6,0x3bf73c00,0xbbfbbbf9,0xac832d4c,
0x35da3775,0x3b723b14,0xba27b943,0x391d3a07,0x30e4342c,0x3be83bb9,0xbb72bae3,0x35da3812,0xac51297f,0x3bfb3bfe,0xbbfdbbd1,0x2b1132d2,0xb48db1aa,0x3bab3be0,0xbbb9bbf5,0xb42caeaa,
0x32ea3540,0x3bd03b8f,0xbae0ba1b,0x3817392b,0xa3db2e78,0x3c003bf6,0xbbd5bb74,0x328835ce,0xb3dfb036,0x3bc13bee,0xbbf0bbfe,0xb004291b,0xb76ab5b6,0x3b173b79,0xbb2ebbaa,0xb710b499,
0x2bd931db,0x3bfc3bdd,0xbb6ebad0,0x35f13832,0xb1dbabd9,0x3bdd3bfc,0xbbffbbd4,0x28b632a1,0xb6aab4d5,0x3b463ba0,0xbba0bbed,0xb4d5b04e,0xb900b832,0x3a3f3ad0,0xba5ebb1a,0xb8d8b75e,
0xae142852,0x3bf73bff,0xbbcdbb5d,0x331b3642,0xb587b31b,0x3b823bcd,0xbbeebbfe,0xb03629e3,0xb896b76a,0x3a8e3b17,0xbb11bb9e,0xb780b4e1,0xba1bb964,0x392b39e9,0xb951ba4b,0xb9fab8f1,
0xb3f7af72,0x3bc03bf2,0xbbfbbbc0,0x2c5133f7,0xb7f9b608,0x3af03b69,0xbba4bbf2,0xb4bdaf72,0xb9b1b8e2,0x399f3a56,0xba47bb14,0xb8f6b775,0xbafcba65,0x37cd38ce,0xb812b943,0xbae3ba07,
0xb659b438,0x3b583bb7,0xbbf8bbf6,0xadb02e78,0xb918b82d,0x3a2b3ad3,0xbb22bbb1,0xb73db469,0xba9cb9e9,0x38813964,0xb948ba52,0xba02b8e7,0xbb9bbb2e,0x34f93710,0xb558b80d,0xbb8abae6,
0xb848b67c,0x3ac23b50,0xbbc3bbfe,0xb3c6aa48,0xba0fb93a,0x393a3a0f,0xba6dbb3b,0xb8c4b6d7,0xbb50bac2,0x367c3848,0xb81db95f,0xbaddb9ed,0xbbf1bbb6,0x2fd63444,0xb0b2b564,0xbbeabb88,
0x319831a6,0x2ebd2f99,0x319831a6,0x2ebd2f99,0x3154317d,0x2cd62dd1,0x3154317d,0x2cd62dd1,0x30da311d,0x297f2b9f,0x30da311d,0x297f2b9f,0x3031308b,0x207126a4,0x3031308b,0x207126a4,
0x311d3198,0xb154b08b,0x311d3198,0xb154b08b,0x2dd13031,0xb17db1a6,0x2dd13031,0xb17db1a6,0xa071297f,0xaf99b0da,0xa071297f,0xaf99b0da,0xaebdab9f,0xa6a4acd6,0xaebdab9f,0xa6a4acd6,
0x3031317d,0xa071add1,0x3031317d,0xa071add1,0xa6a42b9f,0x308b2cd6,0xa6a42b9f,0x308b2cd6,0xb11daebd,0x31543198,0xb11daebd,0x31543198,0xb0dab1a6,0x297f2f99,0xb0dab1a6,0x297f2f99,
0x2dd13154,0x317d311d,0x2dd13154,0x317d311d,0xb031a6a4,0xa0712ebd,0xb031a6a4,0xa0712ebd,0xb08bb1a6,0xb198af99,0xb08bb1a6,0xb198af99,0x2cd6a97f,0xab9fb0da,0x2cd6a97f,0xab9fb0da,
0x297f311d,0xadd12b9f,0x297f311d,0xadd12b9f,0xb1a6aebd,0xb031b198,0xb1a6aebd,0xb031b198,0x26a4af99,0x308b2071,0x26a4af99,0x308b2071,0x315430da,0x2cd6317d,0x315430da,0x2cd6317d,
0xa07130da,0xaf99b17d,0xa07130da,0xaf99b17d,0xb08bb11d,0x31982b9f,0xb08bb11d,0x31982b9f,0x315426a4,0xacd62ebd,0x315426a4,0xacd62ebd,0xa97f3031,0xadd1b1a6,0xa97f3031,0xadd1b1a6,
0xab9f308b,0x311da6a4,0xab9f308b,0x311da6a4,0xa97fb1a6,0xadd12f99,0xa97fb1a6,0xadd12f99,0x303130da,0xa071b17d,0x303130da,0xa071b17d,0xb198acd6,0x2ebd3154,0xb198acd6,0x2ebd3154,
0xaebd3031,0x26a431a6,0xaebd3031,0x26a431a6,0x2cd6b0da,0xab9fb17d,0x2cd6b0da,0xab9fb17d,0xa97f3154,0x2dd1311d,0xa97f3154,0x2dd1311d,0x2071b198,0xaf99b08b,0x2071b198,0xaf99b08b,
0xb08b2f99,0xb198a071,0xb08b2f99,0xb198a071,0x311dadd1,0x3154297f,0x311dadd1,0x3154297f,0xb17d2b9f,0xb0daacd6,0xb17d2b9f,0xb0daacd6,0x31a6a6a4,0x30312ebd,0x31a6a6a4,0x30312ebd,
0xb1542ebd,0x2cd6b198,0xb1542ebd,0x2cd6b198,0x317da071,0xb0da3031,0x317da071,0xb0da3031,0xaf99add1,0x31a6a97f,0xaf99add1,0x31a6a97f,0x26a4311d,0xb08bab9f,0x26a4311d,0xb08bab9f,
0xb1a62dd1,0x3031297f,0xb1a62dd1,0x3031297f,0x2ebd2cd6,0x26a4b154,0x2ebd2cd6,0x26a4b154,0x2b9fb198,0xb11d308b,0x2b9fb198,0xb11d308b,0xb17d2f99,0x30da2071,0xb17d2f99,0x30da2071,
0xb17d2cd6,0xb0da3154,0xb17d2cd6,0xb0da3154,0xa071308b,0x2f9926a4,0xa071308b,0x2f9926a4,0x3198b031,0x2ebdb1a6,0x3198b031,0x2ebdb1a6,0xab9fadd1,0xb11d297f,0xab9fadd1,0xb11d297f,
0xb0da2b9f,0xa97facd6,0xb0da2b9f,0xa97facd6,0xaf993198,0xb1a6308b,0xaf993198,0xb1a6308b,0x2ebd2071,0xa6a43031,0x2ebd2071,0xa6a43031,0x311db17d,0x3154add1,0x311db17d,0x3154add1,
0xaf99297f,0x31a6b0da,0xaf99297f,0x31a6b0da,0xb1983154,0x2ebdb11d,0xb1983154,0x2ebdb11d,0xacd6308b,0xab9fa6a4,0xacd6308b,0xab9fa6a4,0x2dd1a071,0xb17d3031,0x2dd1a071,0xb17d3031,
0xacd626a4,0xab9f2ebd,0xacd626a4,0xab9f2ebd,0xb0da2f99,0x297f2071,0xb0da2f99,0x297f2071,0xb1a6317d,0x3031add1,0xb1a6317d,0x3031add1,0xb08b3154,0x3198b11d,0xb08b3154,0x3198b11d,
0xa6a42071,0xb08b3031,0xa6a42071,0xb08b3031,0xab9f297f,0xb11d30da,0xab9f297f,0xb11d30da,0xadd12cd6,0xb17d3154,0xadd12cd6,0xb17d3154,0xaf992ebd,0xb1a63198,0xaf992ebd,0xb1a63198,
0x26a42071,0x308b3031,0xa6a4a071,0xb08bb031,0x2b9f297f,0x311d30da,0xab9fa97f,0xb11db0da,0x2dd12cd6,0x317d3154,0xadd1acd6,0xb17db154,0x2f992ebd,0x31a63198,0xaf99aebd,0xb1a6b198,
0x2cd626a4,0x2b9f2ebd,0xacd6a6a4,0xab9faebd,0x30da2f99,0xa97f2071,0xb0daaf99,0x297fa071,0x31a6317d,0xb031add1,0xb1a6b17d,0x30312dd1,0x308b3154,0xb198b11d,0xb08bb154,0x3198311d,
0x2f99297f,0xb1a6b0da,0xaf99a97f,0x31a630da,0x31983154,0xaebdb11d,0xb198b154,0x2ebd311d,0x2cd6308b,0x2b9fa6a4,0xacd6b08b,0xab9f26a4,0xadd1a071,0x317d3031,0x2dd12071,0xb17db031,
0x30da2b9f,0x297facd6,0xb0daab9f,0xa97f2cd6,0x2f993198,0x31a6308b,0xaf99b198,0xb1a6b08b,0xaebd2071,0x26a43031,0x2ebda071,0xa6a4b031,0xb11db17d,0xb154add1,0x311d317d,0x31542dd1,
0x317d2cd6,0x30da3154,0xb17dacd6,0xb0dab154,0x2071308b,0xaf9926a4,0xa071b08b,0x2f99a6a4,0xb198b031,0xaebdb1a6,0x31983031,0x2ebd31a6,0x2b9fadd1,0x311d297f,0xab9f2dd1,0xb11da97f,
0x31a62dd1,0xb031297f,0xb1a6add1,0x3031a97f,0xaebd2cd6,0xa6a4b154,0x2ebdacd6,0x26a43154,0xab9fb198,0x311d308b,0x2b9f3198,0xb11db08b,0x317d2f99,0xb0da2071,0xb17daf99,0x30daa071,
0x31542ebd,0xacd6b198,0xb154aebd,0x2cd63198,0xb17da071,0x30da3031,0x317d2071,0xb0dab031,0x2f99add1,0xb1a6a97f,0xaf992dd1,0x31a6297f,0xa6a4311d,0x308bab9f,0x26a4b11d,0xb08b2b9f,
0x308b2f99,0x3198a071,0xb08baf99,0xb1982071,0xb11dadd1,0xb154297f,0x311d2dd1,0x3154a97f,0x317d2b9f,0x30daacd6,0xb17dab9f,0xb0da2cd6,0xb1a6a6a4,0xb0312ebd,0x31a626a4,0x3031aebd,
0x2ebd3031,0xa6a431a6,0xaebdb031,0x26a4b1a6,0xacd6b0da,0x2b9fb17d,0x2cd630da,0xab9f317d,0x297f3154,0xadd1311d,0xa97fb154,0x2dd1b11d,0xa071b198,0x2f99b08b,0x20713198,0xaf99308b,
0x2b9f308b,0xb11da6a4,0xab9fb08b,0x311d26a4,0x297fb1a6,0x2dd12f99,0xa97f31a6,0xadd1af99,0xb03130da,0x2071b17d,0x3031b0da,0xa071317d,0x3198acd6,0xaebd3154,0xb1982cd6,0x2ebdb154,
0x207130da,0x2f99b17d,0xa071b0da,0xaf99317d,0x308bb11d,0xb1982b9f,0xb08b311d,0x3198ab9f,0xb15426a4,0x2cd62ebd,0x3154a6a4,0xacd6aebd,0x297f3031,0x2dd1b1a6,0xa97fb031,0xadd131a6,
0xa97f311d,0x2dd12b9f,0x297fb11d,0xadd1ab9f,0x31a6aebd,0x3031b198,0xb1a62ebd,0xb0313198,0xa6a4af99,0xb08b2071,0x26a42f99,0x308ba071,0xb15430da,0xacd6317d,0x3154b0da,0x2cd6b17d,
0xadd13154,0xb17d311d,0x2dd1b154,0x317db11d,0x3031a6a4,0x20712ebd,0xb03126a4,0xa071aebd,0x308bb1a6,0x3198af99,0xb08b31a6,0xb1982f99,0xacd6a97f,0x2b9fb0da,0x2cd6297f,0xab9f30da,
0xb031317d,0x2071add1,0x3031b17d,0xa0712dd1,0x26a42b9f,0xb08b2cd6,0xa6a4ab9f,0x308bacd6,0x311daebd,0xb1543198,0xb11d2ebd,0x3154b198,0x30dab1a6,0xa97f2f99,0xb0da31a6,0x297faf99,
0xb11d3198,0x3154b08b,0x311db198,0xb154308b,0xadd13031,0x317db1a6,0x2dd1b031,0xb17d31a6,0x2071297f,0x2f99b0da,0xa071a97f,0xaf9930da,0x2ebdab9f,0x26a4acd6,0xaebd2b9f,0xa6a42cd6,
0xb19831a6,0xaebd2f99,0x3198b1a6,0x2ebdaf99,0xb154317d,0xacd62dd1,0x3154b17d,0x2cd6add1,0xb0da311d,0xa97f2b9f,0x30dab11d,0x297fab9f,0xb031308b,0xa07126a4,0x3031b08b,0x2071a6a4,
0x319831a6,0x3031317d,0x2ebd2f99,0xa071add1,0x3154317d,0xa6a42b9f,0x2cd62dd1,0x308b2cd6,0x30da311d,0xb11daebd,0x297f2b9f,0x31543198,0x3031308b,0xb0dab1a6,0x207126a4,0x297f2f99,
0x311d3198,0x2dd13154,0xb154b08b,0x317d311d,0x2dd13031,0xb031a6a4,0xb17db1a6,0xa0712ebd,0xa071297f,0xb08bb1a6,0xaf99b0da,0xb198af99,0xaebdab9f,0x2cd6a97f,0xa6a4acd6,0xab9fb0da,
0x297f311d,0xab9f308b,0xadd12b9f,0x311da6a4,0xb1a6aebd,0xa97fb1a6,0xb031b198,0xadd12f99,0x26a4af99,0x303130da,0x308b2071,0xa071b17d,0x315430da,0xb198acd6,0x2cd6317d,0x2ebd3154,
0xa07130da,0xaebd3031,0xaf99b17d,0x26a431a6,0xb08bb11d,0x2cd6b0da,0x31982b9f,0xab9fb17d,0x315426a4,0xa97f3154,0xacd62ebd,0x2dd1311d,0xa97f3031,0x2071b198,0xadd1b1a6,0xaf99b08b,
0xb08b2f99,0xb1a62dd1,0xb198a071,0x3031297f,0x311dadd1,0x2ebd2cd6,0x3154297f,0x26a4b154,0xb17d2b9f,0x2b9fb198,0xb0daacd6,0xb11d308b,0x31a6a6a4,0xb17d2f99,0x30312ebd,0x30da2071,
0xb1542ebd,0xb17d2cd6,0x2cd6b198,0xb0da3154,0x317da071,0xa071308b,0xb0da3031,0x2f9926a4,0xaf99add1,0x3198b031,0x31a6a97f,0x2ebdb1a6,0x26a4311d,0xab9fadd1,0xb08bab9f,0xb11d297f,
0xb0da2b9f,0xacd626a4,0xa97facd6,0xab9f2ebd,0xaf993198,0xb0da2f99,0xb1a6308b,0x297f2071,0x2ebd2071,0xb1a6317d,0xa6a43031,0x3031add1,0x311db17d,0xb08b3154,0x3154add1,0x3198b11d,
0xaf99297f,0xa6a42071,0x31a6b0da,0xb08b3031,0xb1983154,0xab9f297f,0x2ebdb11d,0xb11d30da,0xacd6308b,0xadd12cd6,0xab9fa6a4,0xb17d3154,0x2dd1a071,0xaf992ebd,0xb17d3031,0xb1a63198,
0x319831a6,0x3031317d,0x2ebd2f99,0xa071add1,0x3154317d,0xa6a42b9f,0x2cd62dd1,0x308b2cd6,0x30da311d,0xb11daebd,0x297f2b9f,0x31543198,0x3031308b,0xb0dab1a6,0x207126a4,0x297f2f99,
0x311d3198,0x2dd13154,0xb154b08b,0x317d311d,0x2dd13031,0xb031a6a4,0xb17db1a6,0xa0712ebd,0xa071297f,0xb08bb1a6,0xaf99b0da,0xb198af99,0xaebdab9f,0x2cd6a97f,0xa6a4acd6,0xab9fb0da,
0x297f311d,0xab9f308b,0xadd12b9f,0x311da6a4,0xb1a6aebd,0xa97fb1a6,0xb031b198,0xadd12f99,0x26a4af99,0x303130da,0x308b2071,0xa071b17d,0x315430da,0xb198acd6,0x2cd6317d,0x2ebd3154,
0xa07130da,0xaebd3031,0xaf99b17d,0x26a431a6,0xb08bb11d,0x2cd6b0da,0x31982b9f,0xab9fb17d,0x315426a4,0xa97f3154,0xacd62ebd,0x2dd1311d,0xa97f3031,0x2071b198,0xadd1b1a6,0xaf99b08b,
0xb08b2f99,0xb1a62dd1,0xb198a071,0x3031297f,0x311dadd1,0x2ebd2cd6,0x3154297f,0x26a4b154,0xb17d2b9f,0x2b9fb198,0xb0daacd6,0xb11d308b,0x31a6a6a4,0xb17d2f99,0x30312ebd,0x30da2071,
0xb1542ebd,0xb17d2cd6,0x2cd6b198,0xb0da3154,0x317da071,0xa071308b,0xb0da3031,0x2f9926a4,0xaf99add1,0x3198b031,0x31a6a97f,0x2ebdb1a6,0x26a4311d,0xab9fadd1,0xb08bab9f,0xb11d297f,
0xb0da2b9f,0xacd626a4,0xa97facd6,0xab9f2ebd,0xaf993198,0xb0da2f99,0xb1a6308b,0x297f2071,0x2ebd2071,0xb1a6317d,0xa6a43031,0x3031add1,0x311db17d,0xb08b3154,0x3154add1,0x3198b11d,
0xaf99297f,0xa6a42071,0x31a6b0da,0xb08b3031,0xb1983154,0xab9f297f,0x2ebdb11d,0xb11d30da,0xacd6308b,0xadd12cd6,0xab9fa6a4,0xb17d3154,0x2dd1a071,0xaf992ebd,0xb17d3031,0xb1a63198,
0x26a42071,0x2f99297f,0x308b3031,0xb1a6b0da,0x2b9f297f,0x31983154,0x311d30da,0xaebdb11d,0x2dd12cd6,0x2cd6308b,0x317d3154,0x2b9fa6a4,0x2f992ebd,0xadd1a071,0x31a63198,0x317d3031,
0x2cd626a4,0x30da2b9f,0x2b9f2ebd,0x297facd6,0x30da2f99,0x2f993198,0xa97f2071,0x31a6308b,0x31a6317d,0xaebd2071,0xb031add1,0x26a43031,0x308b3154,0xb11db17d,0xb198b11d,0xb154add1,
0x317d2cd6,0x31542ebd,0x30da3154,0xacd6b198,0x2071308b,0xb17da071,0xaf9926a4,0x30da3031,0xb198b031,0x2f99add1,0xaebdb1a6,0xb1a6a97f,0x2b9fadd1,0xa6a4311d,0x311d297f,0x308bab9f,
0x31a62dd1,0x308b2f99,0xb031297f,0x3198a071,0xaebd2cd6,0xb11dadd1,0xa6a4b154,0xb154297f,0xab9fb198,0x317d2b9f,0x311d308b,0x30daacd6,0x317d2f99,0xb1a6a6a4,0xb0da2071,0xb0312ebd,
0x2ebd3031,0x207130da,0xa6a431a6,0x2f99b17d,0xacd6b0da,0x308bb11d,0x2b9fb17d,0xb1982b9f,0x297f3154,0xb15426a4,0xadd1311d,0x2cd62ebd,0xa071b198,0x297f3031,0x2f99b08b,0x2dd1b1a6,
0x2b9f308b,0xa97f311d,0xb11da6a4,0x2dd12b9f,0x297fb1a6,0x31a6aebd,0x2dd12f99,0x3031b198,0xb03130da,0xa6a4af99,0x2071b17d,0xb08b2071,0x3198acd6,0xb15430da,0xaebd3154,0xacd6317d,
0xadd13154,0xb11d3198,0xb17d311d,0x3154b08b,0x3031a6a4,0xadd13031,0x20712ebd,0x317db1a6,0x308bb1a6,0x2071297f,0x3198af99,0x2f99b0da,0xacd6a97f,0x2ebdab9f,0x2b9fb0da,0x26a4acd6,
0xb031317d,0xb19831a6,0x2071add1,0xaebd2f99,0x26a42b9f,0xb154317d,0xb08b2cd6,0xacd62dd1,0x311daebd,0xb0da311d,0xb1543198,0xa97f2b9f,0x30dab1a6,0xb031308b,0xa97f2f99,0xa07126a4,
0xa6a4a071,0xaf99a97f,0xb08bb031,0x31a630da,0xab9fa97f,0xb198b154,0xb11db0da,0x2ebd311d,0xadd1acd6,0xacd6b08b,0xb17db154,0xab9f26a4,0xaf99aebd,0x2dd12071,0xb1a6b198,0xb17db031,
0xacd6a6a4,0xb0daab9f,0xab9faebd,0xa97f2cd6,0xb0daaf99,0xaf99b198,0x297fa071,0xb1a6b08b,0xb1a6b17d,0x2ebda071,0x30312dd1,0xa6a4b031,0xb08bb154,0x311d317d,0x3198311d,0x31542dd1,
0xb17dacd6,0xb154aebd,0xb0dab154,0x2cd63198,0xa071b08b,0x317d2071,0x2f99a6a4,0xb0dab031,0x31983031,0xaf992dd1,0x2ebd31a6,0x31a6297f,0xab9f2dd1,0x26a4b11d,0xb11da97f,0xb08b2b9f,
0xb1a6add1,0xb08baf99,0x3031a97f,0xb1982071,0x2ebdacd6,0x311d2dd1,0x26a43154,0x3154a97f,0x2b9f3198,0xb17dab9f,0xb11db08b,0xb0da2cd6,0xb17daf99,0x31a626a4,0x30daa071,0x3031aebd,
0xaebdb031,0xa071b0da,0x26a4b1a6,0xaf99317d,0x2cd630da,0xb08b311d,0xab9f317d,0x3198ab9f,0xa97fb154,0x3154a6a4,0x2dd1b11d,0xacd6aebd,0x20713198,0xa97fb031,0xaf99308b,0xadd131a6,
0xab9fb08b,0x297fb11d,0x311d26a4,0xadd1ab9f,0xa97f31a6,0xb1a62ebd,0xadd1af99,0xb0313198,0x3031b0da,0x26a42f99,0xa071317d,0x308ba071,0xb1982cd6,0x3154b0da,0x2ebdb154,0x2cd6b17d,
0x2dd1b154,0x311db198,0x317db11d,0xb154308b,0xb03126a4,0x2dd1b031,0xa071aebd,0xb17d31a6,0xb08b31a6,0xa071a97f,0xb1982f99,0xaf9930da,0x2cd6297f,0xaebd2b9f,0xab9f30da,0xa6a42cd6,
0x3031b17d,0x3198b1a6,0xa0712dd1,0x2ebdaf99,0xa6a4ab9f,0x3154b17d,0x308bacd6,0x2cd6add1,0xb11d2ebd,0x30dab11d,0x3154b198,0x297fab9f,0xb0da31a6,0x3031b08b,0x297faf99,0x2071a6a4,
0xb198b1a6,0xb031b17d,0xaebdaf99,0x20712dd1,0xb154b17d,0x26a4ab9f,0xacd6add1,0xb08bacd6,0xb0dab11d,0x311d2ebd,0xa97fab9f,0xb154b198,0xb031b08b,0x30da31a6,0xa071a6a4,0xa97faf99,
0xb11db198,0xadd1b154,0x3154308b,0xb17db11d,0xadd1b031,0x303126a4,0x317d31a6,0x2071aebd,0x2071a97f,0x308b31a6,0x2f9930da,0x31982f99,0x2ebd2b9f,0xacd6297f,0x26a42cd6,0x2b9f30da,
0xa97fb11d,0x2b9fb08b,0x2dd1ab9f,0xb11d26a4,0x31a62ebd,0x297f31a6,0x30313198,0x2dd1af99,0xa6a42f99,0xb031b0da,0xb08ba071,0x2071317d,0xb154b0da,0x31982cd6,0xacd6b17d,0xaebdb154,
0x2071b0da,0x2ebdb031,0x2f99317d,0xa6a4b1a6,0x308b311d,0xacd630da,0xb198ab9f,0x2b9f317d,0xb154a6a4,0x297fb154,0x2cd6aebd,0xadd1b11d,0x297fb031,0xa0713198,0x2dd131a6,0x2f99308b,
0x308baf99,0x31a6add1,0x31982071,0xb031a97f,0xb11d2dd1,0xaebdacd6,0xb154a97f,0xa6a43154,0x317dab9f,0xab9f3198,0x30da2cd6,0x311db08b,0xb1a626a4,0x317daf99,0xb031aebd,0xb0daa071,
0x3154aebd,0x317dacd6,0xacd63198,0x30dab154,0xb17d2071,0x2071b08b,0x30dab031,0xaf99a6a4,0x2f992dd1,0xb1983031,0xb1a6297f,0xaebd31a6,0xa6a4b11d,0x2b9f2dd1,0x308b2b9f,0x311da97f,
0x30daab9f,0x2cd6a6a4,0x297f2cd6,0x2b9faebd,0x2f99b198,0x30daaf99,0x31a6b08b,0xa97fa071,0xaebda071,0x31a6b17d,0x26a4b031,0xb0312dd1,0xb11d317d,0x308bb154,0xb1542dd1,0xb198311d,
0x2f99a97f,0x26a4a071,0xb1a630da,0x308bb031,0x3198b154,0x2b9fa97f,0xaebd311d,0x311db0da,0x2cd6b08b,0x2dd1acd6,0x2b9f26a4,0x317db154,0xadd12071,0x2f99aebd,0x317db031,0x31a6b198,
0x26a42071,0x2f99297f,0x308b3031,0xb1a6b0da,0x2b9f297f,0x31983154,0x311d30da,0xaebdb11d,0x2dd12cd6,0x2cd6308b,0x317d3154,0x2b9fa6a4,0x2f992ebd,0xadd1a071,0x31a63198,0x317d3031,
0x2cd626a4,0x30da2b9f,0x2b9f2ebd,0x297facd6,0x30da2f99,0x2f993198,0xa97f2071,0x31a6308b,0x31a6317d,0xaebd2071,0xb031add1,0x26a43031,0x308b3154,0xb11db17d,0xb198b11d,0xb154add1,
0x317d2cd6,0x31542ebd,0x30da3154,0xacd6b198,0x2071308b,0xb17da071,0xaf9926a4,0x30da3031,0xb198b031,0x2f99add1,0xaebdb1a6,0xb1a6a97f,0x2b9fadd1,0xa6a4311d,0x311d297f,0x308bab9f,
0x31a62dd1,0x308b2f99,0xb031297f,0x3198a071,0xaebd2cd6,0xb11dadd1,0xa6a4b154,0xb154297f,0xab9fb198,0x317d2b9f,0x311d308b,0x30daacd6,0x317d2f99,0xb1a6a6a4,0xb0da2071,0xb0312ebd,
0x2ebd3031,0x207130da,0xa6a431a6,0x2f99b17d,0xacd6b0da,0x308bb11d,0x2b9fb17d,0xb1982b9f,0x297f3154,0xb15426a4,0xadd1311d,0x2cd62ebd,0xa071b198,0x297f3031,0x2f99b08b,0x2dd1b1a6,
0x2b9f308b,0xa97f311d,0xb11da6a4,0x2dd12b9f,0x297fb1a6,0x31a6aebd,0x2dd12f99,0x3031b198,0xb03130da,0xa6a4af99,0x2071b17d,0xb08b2071,0x3198acd6,0xb15430da,0xaebd3154,0xacd6317d,
0xadd13154,0xb11d3198,0xb17d311d,0x3154b08b,0x3031a6a4,0xadd13031,0x20712ebd,0x317db1a6,0x308bb1a6,0x2071297f,0x3198af99,0x2f99b0da,0xacd6a97f,0x2ebdab9f,0x2b9fb0da,0x26a4acd6,
0xb031317d,0xb19831a6,0x2071add1,0xaebd2f99,0x26a42b9f,0xb154317d,0xb08b2cd6,0xacd62dd1,0x311daebd,0xb0da311d,0xb1543198,0xa97f2b9f,0x30dab1a6,0xb031308b,0xa97f2f99,0xa07126a4,
0x3bfe3bfe,0xaa48aa48,0x3bc93bc3,0xb365b3c6,0x3bfe3bfe,0xaa48aa48,0x3bd43bce,0xb2a1b303,0x3bfe3bfe,0xaa48aa48,0x3bdd3bd9,0xb1dbb23e,0x3bfe3bfe,0xaa48aa48,0x3be63be2,0xb115b179,
0x3bec3bea,0xb080b0b2,0x3b953b88,0xb51db564,0x3bef3bed,0xb01db04e,0x3bab3ba0,0xb48db4d5,0x3bf23bf1,0xaf72afd6,0x3bc03bb6,0xb3f7b444,0x3bf53bf4,0xaeaaaf0e,0x3bd13bc9,0xb2d2b365,
0x3b503b3b,0xb67cb6d7,0x3a993a6d,0xb887b8c4,0x3b773b64,0xb5c2b61f,0x3ae93ac2,0xb807b848,0x3b993b88,0xb505b564,0x3b303b0e,0xb705b78b,0x3bb63ba8,0xb444b4a5,0x3b6e3b50,0xb5f1b67c,
0x3afc3add,0xb7cdb81d,0x3a2739ed,0xb91db95f,0x3b363b1a,0xb6eeb75e,0x3a923a5e,0xb891b8d8,0x3b693b50,0xb608b67c,0x3af03ac2,0xb7f9b848,0x3b953b80,0xb51db593,0x3b413b1a,0xb6c1b75e,
0x39a8395f,0xb9a8b9ed,0x3887381d,0xba99badd,0x3a2f39ed,0xb913b95f,0x394d38ec,0xb9feba4f,0x3aa73a6d,0xb872b8c4,0x39fe39a8,0xb94db9a8,0x3b0e3add,0xb78bb81d,0x3a993a4f,0xb887b8ec,
0x391d38c4,0xba27ba6d,0x37cd36d7,0xbafcbb3b,0x39c33972,0xb98db9dc,0x38ce385d,0xba65bab5,0x3a563a0f,0xb8e2b93a,0x399f393a,0xb9b1ba0f,0x3ad63a99,0xb828b887,0x3a5639fe,0xb8e2b94d,
0x367c3564,0xbb50bb88,0x336530b2,0xbbc9bbea,0x3848378b,0xbac2bb0e,0x364e3505,0xbb5abb99,0x393a38c4,0xba0fba6d,0x385d378b,0xbab5bb0e,0x3a0f39a8,0xb93ab9a8,0x397238ec,0xb9dcba4f,
0x351d33c6,0xbb95bbc3,0x30802a48,0xbbecbbfe,0x3775364e,0xbb14bb5a,0x351d3365,0xbb95bbc9,0x38ce3848,0xba65bac2,0x37cd367c,0xbafcbb50,0x39c3394d,0xb98db9fe,0x391d3887,0xba27ba99,
0x3bfe3bfe,0xaa48aa48,0x3bed3bea,0xb04eb0b2,0x3bfe3bfe,0xaa48aa48,0x3bf43bf1,0xaf0eafd6,0x3bfe3bfe,0xaa48aa48,0x3bf83bf6,0xad7eae46,0x3bfe3bfe,0xaa48aa48,0x3bfc3bfa,0xabd9acb5,
0x3bf73bf6,0xade2ae46,0x3be03bd9,0xb1aab23e,0x3bf93bf8,0xad1aad7e,0x3bec3be6,0xb080b115,0x3bfb3bfa,0xac51acb5,0x3bf53bf1,0xaeaaafd6,0x3bfd3bfc,0xab11abd9,0x3bfb3bf8,0xac51ad7e,
0x3bce3bc3,0xb303b3c6,0x3ba03b88,0xb4d5b564,0x3be23bd9,0xb179b23e,0x3bc93bb6,0xb365b444,0x3bf13bea,0xafd6b0b2,0x3be63bd9,0xb115b23e,0x3bfa3bf6,0xacb5ae46,0x3bf83bf1,0xad7eafd6,
0x3bb93ba8,0xb42cb4a5,0x3b843b64,0xb57cb61f,0x3bd63bc9,0xb26fb365,0x3bb93ba0,0xb42cb4d5,0x3bec3be2,0xb080b179,0x3be03bce,0xb1aab303,0x3bf93bf4,0xad1aaf0e,0x3bf73bed,0xade2b04e,
0x3b643b3b,0xb61fb6d7,0x3b1a3add,0xb75eb81d,0x3ba83b88,0xb4a5b564,0x3b803b50,0xb593b67c,0x3bd93bc3,0xb23eb3c6,0x3bc93ba8,0xb365b4a5,0x3bf63bea,0xae46b0b2,0x3bf43be2,0xaf0eb179,
0x3b413b0e,0xb6c1b78b,0x3af03aa7,0xb7f9b872,0x3b953b6e,0xb51db5f1,0x3b693b30,0xb608b705,0x3bd13bb6,0xb2d2b444,0x3bc03b99,0xb3f7b505,0x3bf53be6,0xaeaab115,0x3bf23bdd,0xaf72b1db,
0x3ac23a6d,0xb848b8c4,0x3a5e39ed,0xb8d8b95f,0x3b503b0e,0xb67cb78b,0x3b1a3ac2,0xb75eb848,0x3bb63b88,0xb444b564,0x3ba03b64,0xb4d5b61f,0x3bf13bd9,0xafd6b23e,0x3bed3bce,0xb04eb303,
0x3a923a2f,0xb891b913,0x3a2739a8,0xb91db9a8,0x3b363ae9,0xb6eeb807,0x3afc3a99,0xb7cdb887,0x3bab3b77,0xb48db5c2,0x3b953b50,0xb51db67c,0x3bef3bd4,0xb01db2a1,0x3bec3bc9,0xb080b365,
0x3bc63bfe,0x33962a48,0x3b4b3bc3,0x369333c6,0x3a833b46,0x38a636aa,0x39b13a99,0x399f3887,0x38523984,0x3abc39cb,0x36c1389b,0x3b413a8a,0x320d35f1,0x3bdb3b6e,0x2d1a3414,0x3bf93bbc,
0x3b913bea,0x353430b2,0x3af63b88,0x37e33564,0x3a1f3af6,0x392737e3,0x393a3a2f,0x3a0f3913,0x37b73913,0x3b023a2f,0x35c2381d,0x3b773add,0x304e3505,0x3bed3b99,0x2648323e,0x3bff3bd9,
0x3a923b3b,0x389136d7,0x399f3a6d,0x39b138c4,0x38ba39ba,0x3a743996,0x374838b0,0x3b203a7c,0x34bd3732,0x3ba43b25,0x31473505,0x3be43b99,0xa7da304e,0x3bff3bed,0xb0802248,0x3bec3c00,
0x3a1f3add,0x3927381d,0x391339ed,0x3a2f395f,0x3832393a,0x3ad03a0f,0x361f381d,0x3b643add,0x3365361f,0x3bc93b64,0x2e4633c6,0x3bf63bc3,0xad7e2cb5,0x3bf83bfa,0xb23eaa48,0x3bd93bfe,
0x387c395f,0x3aa039ed,0x3665381d,0x3b553add,0x34ed3705,0x3b9d3b30,0x30e43475,0x3be83baf,0x27da3179,0x3bff3be2,0xaeaa2648,0x3bf53bff,0xb3f7af0e,0x3bc03bf4,0xb5abb365,0x3b7b3bc9,
0x37b738c4,0x3b023a6d,0x350536d7,0x3b993b3b,0x336535c2,0x3bc93b77,0x2cb5323e,0x3bfa3bd9,0xa8b62e46,0x3bff3bf6,0xb179aa48,0x3be23bfe,0xb4d5b179,0x3ba03be2,0xb67cb4a5,0x3b503ba8,
0x33343564,0x3bcb3b88,0x297f30b2,0x3bfe3bea,0x9e482f0e,0x3c003bf4,0xb147abd9,0x3be43bfc,0xb396afd6,0x3bc63bf1,0xb5dab444,0x3b723bb6,0xb748b593,0x3b203b80,0xb867b75e,0x3aae3b1a,
0x304e33c6,0x3bed3bc3,0xaa482a48,0x3bfe3bfe,0xad7e2648,0x3bf83bff,0xb3c6b0b2,0x3bc33bea,0xb4d5b23e,0x3ba03bd9,0xb6d7b564,0x3b3b3b88,0xb807b67c,0x3ae93b50,0xb8c4b81d,0x3a6d3add,
0xb20d8000,0x3bdb3c00,0xb45dae46,0x3bb23bf6,0xb852b5f1,0x3abc3b6e,0xb8bab705,0x3a743b30,0xba83b984,0x38a639cb,0xbaaeb9cb,0x38673984,0xbbc6bb46,0x339636aa,0xbbcbbb5a,0x3334364e,
0xb365aa48,0x3bc93bfe,0xb505b0b2,0x3b993bea,0xb887b67c,0x3a993b50,0xb8ecb78b,0x3a4f3b0e,0xba99b9a8,0x388739a8,0xbac2b9ed,0x3848395f,0xbbc9bb50,0x3365367c,0xbbcebb64,0x3303361f,
0xb5abb23e,0x3b7b3bd9,0xb6eeb4a5,0x3b363ba8,0xb91db807,0x3a273ae9,0xb97bb887,0x39d43a99,0xbad6ba0f,0x3828393a,0xbafcba4f,0x37cd38ec,0xbbd1bb6e,0x32d235f1,0xbbd6bb80,0x326f3593,
0xb64eb3c6,0x3b5a3bc3,0xb78bb564,0x3b0e3b88,0xb94db848,0x39fe3ac2,0xb9a8b8c4,0x39a83a6d,0xbae9ba2f,0x38073913,0xbb0eba6d,0x378b38c4,0xbbd4bb77,0x32a135c2,0xbbd9bb88,0x323e3564,
0xb812b61f,0x3ae33b64,0xb8a6b78b,0x3a833b0e,0xb9d4b900,0x397b3a3f,0xba27b972,0x391d39dc,0xbb20ba8a,0x3748389b,0xbb41bac2,0x36c13848,0xbbdbbb91,0x320d3534,0xbbe0bba0,0x31aa34d5,
0xb85db6d7,0x3ab53b3b,0xb8ecb81d,0x3a4f3add,0xb9feb93a,0x394d3a0f,0xba4fb9a8,0x38ec39a8,0xbb30baa7,0x37053872,0xbb50badd,0x367c381d,0xbbddbb99,0x31db3505,0xbbe2bba8,0x317934a5,
0xb930b872,0x3a173aa7,0xb9b1b913,0x399f3a2f,0xba74b9dc,0x38ba3972,0xbabcba3f,0x38523900,0xbb5fbaf6,0x363737e3,0xbb7bbb25,0x35ab3732,0xbbe4bbaf,0x31473475,0xbbe8bbbc,0x30e43414,
0xb972b8c4,0x39dc3a6d,0xb9edb95f,0x395f39ed,0xba99ba0f,0x3887393a,0xbaddba6d,0x381d38c4,0xbb6ebb0e,0x35f1378b,0xbb88bb3b,0x356436d7,0xbbe6bbb6,0x31153444,0xbbeabbc3,0x30b233c6,
0x31a831a8,0x30b4318c,0x31a831a8,0xb0b4b18c,0x31a831a8,0x286a2e49,0x31a831a8,0xa86aae49,0x31a831a8,0xae49a86a,0x31a831a8,0x2e49286a,0x31a831a8,0xb18cb0b4,0x31a831a8,0x318c30b4,
0x316a31a1,0x2f2d316a,0xaa92a470,0x305f2a92,0x305f30fd,0xad552470,0xaf2dad55,0x30fd31a1,0x2d552f2d,0xb1a1b0fd,0xb0fdb05f,0xa4702d55,0x24702a92,0xaa92b05f,0xb1a1b16a,0xb16aaf2d,
0x2c54313a,0xa86a30b4,0x2c54313a,0x286ab0b4,0xb13aac54,0xae49b18c,0xb13aac54,0x2e49318c,0xac54b13a,0x318c2e49,0xac54b13a,0xb18cae49,0x313a2c54,0xb0b4286a,0x313a2c54,0x30b4a86a,
0x247030fd,0xad55305f,0xb1a1ad55,0x30fd2f2d,0xb16ab05f,0x2470b16a,0x2a92af2d,0xb1a1aa92,0x2f2daa92,0x2a9231a1,0x305f316a,0x316aa470,0x2d5531a1,0xaf2db0fd,0xb0fda470,0xb05f2d55,
0xb0003000,0xb18c2e49,0xb0003000,0x318cae49,0x3000b000,0x30b4286a,0x3000b000,0xb0b4a86a,0xb0003000,0xa86ab0b4,0xb0003000,0x286a30b4,0x3000b000,0xae49318c,0x3000b000,0x2e49b18c,
0xb0fd2f2d,0xb1a12d55,0xad55b05f,0xa47030fd,0x31a1aa92,0x2a922f2d,0x2470316a,0x316ab05f,0xb16aa470,0x305fb16a,0x2a92b1a1,0xaf2daa92,0x305f2d55,0xb0fd2470,0xaf2d30fd,0xad5531a1,
0xb13a2c54,0xae49286a,0xb13a2c54,0x2e49a86a,0xac54313a,0xb18c30b4,0xac54313a,0x318cb0b4,0x313aac54,0xb0b4318c,0x313aac54,0x30b4b18c,0x2c54b13a,0xa86a2e49,0x2c54b13a,0x286aae49,
0xb05f2a92,0xaa922470,0x2f2db16a,0xb16a31a1,0xb0fd31a1,0xaf2d2d55,0xad55a470,0xb05f30fd,0x24702d55,0xb0fd305f,0xb1a130fd,0xad552f2d,0x316aaf2d,0xb1a1316a,0xaa92305f,0xa4702a92,
0x80008000,0xae49a86a,0x80008000,0x2e49286a,0x80008000,0xb18cb0b4,0x80008000,0x318c30b4,0x80008000,0xb0b4b18c,0x80008000,0x30b4318c,0x80008000,0xa86aae49,0x80008000,0x286a2e49,
0xaa92a470,0xb05faa92,0xb16ab1a1,0x2f2d316a,0xaf2dad55,0xb0fdb1a1,0xb05fb0fd,0xad552470,0xb0fdb05f,0x2470ad55,0xad55af2d,0xb1a1b0fd,0xb1a1b16a,0x316a2f2d,0xa470aa92,0xaa92b05f,
0xb13aac54,0xb18cae49,0xb13aac54,0x318c2e49,0xac54b13a,0x30b4a86a,0xac54b13a,0xb0b4286a,0x313a2c54,0xa86a30b4,0x313a2c54,0x286ab0b4,0x2c54313a,0xae49b18c,0x2c54313a,0x2e49318c,
0xb1a1ad55,0xb0fdaf2d,0xa470b0fd,0xad55305f,0x2a92af2d,0x31a12a92,0x316a305f,0x2470b16a,0x305f316a,0xb16a2470,0xaf2d2a92,0x2a9231a1,0xb0fda470,0x305fad55,0xad55b1a1,0xaf2db0fd,
0xb000b000,0xa86ab0b4,0xb000b000,0x286a30b4,0x30003000,0xae49318c,0x30003000,0x2e49b18c,0xb000b000,0x318cae49,0xb000b000,0xb18c2e49,0x30003000,0xb0b4a86a,0x30003000,0x30b4286a,
0xad55b05f,0x2470b0fd,0x30fdaf2d,0xb1a12d55,0x2470316a,0xb16a305f,0xb1a12a92,0x2a922f2d,0x2a92b1a1,0x2f2d2a92,0x316a2470,0x305fb16a,0xaf2d30fd,0x2d55b1a1,0xb05fad55,0xb0fd2470,
0x2c54b13a,0x30b4b18c,0x2c54b13a,0xb0b4318c,0xb13a2c54,0x286aae49,0xb13a2c54,0xa86a2e49,0xac54313a,0xae49286a,0xac54313a,0x2e49a86a,0x313aac54,0xb18c30b4,0x313aac54,0x318cb0b4,
0x2f2db16a,0x316ab1a1,0x305faa92,0xaa922470,0xad55a470,0x305fb0fd,0x30fdb1a1,0xaf2d2d55,0xb1a130fd,0x2d55af2d,0xa470ad55,0xb0fd305f,0xaa92305f,0x2470aa92,0xb16a2f2d,0xb1a1316a,
0xb16ab1a1,0xaf2db16a,0x2a922470,0xb05faa92,0xb05fb0fd,0x2d55a470,0x2f2d2d55,0xb0fdb1a1,0xad55af2d,0x31a130fd,0x30fd305f,0x2470ad55,0xa470aa92,0x2a92305f,0x31a1316a,0x316a2f2d,
0xb0b4b18c,0xac54b13a,0x30b4318c,0xac54b13a,0xa86aae49,0x313a2c54,0x286a2e49,0x313a2c54,0x2e49286a,0x2c54313a,0xae49a86a,0x2c54313a,0x318c30b4,0xb13aac54,0xb18cb0b4,0xb13aac54,
0xa470b0fd,0x2d55b05f,0x31a12d55,0xb0fdaf2d,0x316a305f,0xa470316a,0xaa922f2d,0x31a12a92,0xaf2d2a92,0xaa92b1a1,0xb05fb16a,0xb16a2470,0xad55b1a1,0x2f2d30fd,0x30fd2470,0x305fad55,
0x286ab0b4,0x3000b000,0xa86a30b4,0x3000b000,0x2e49318c,0xb0003000,0xae49b18c,0xb0003000,0xb18cae49,0x3000b000,0x318c2e49,0x3000b000,0x30b4a86a,0xb0003000,0xb0b4286a,0xb0003000,
0x30fdaf2d,0x31a1ad55,0x2d55305f,0x2470b0fd,0xb1a12a92,0xaa92af2d,0xa470b16a,0xb16a305f,0x316a2470,0xb05f316a,0xaa9231a1,0x2f2d2a92,0xb05fad55,0x30fda470,0x2f2db0fd,0x2d55b1a1,
0x318cae49,0x313aac54,0xb18c2e49,0x313aac54,0xb0b4a86a,0x2c54b13a,0x30b4286a,0x2c54b13a,0x286a30b4,0xb13a2c54,0xa86ab0b4,0xb13a2c54,0x2e49b18c,0xac54313a,0xae49318c,0xac54313a,
0x305faa92,0x2a92a470,0xaf2d316a,0x316ab1a1,0x30fdb1a1,0x2f2dad55,0x2d552470,0x305fb0fd,0xa470ad55,0x30fdb05f,0x31a1b0fd,0x2d55af2d,0xb16a2f2d,0x31a1b16a,0x2a92b05f,0x2470aa92,
0x2e49a86a,0x80000000,0xae49286a,0x80008000,0x318cb0b4,0x80000000,0xb18c30b4,0x80008000,0x30b4b18c,0x80000000,0xb0b4318c,0x80008000,0x286aae49,0x80008000,0xa86a2e49,0x80008000,
0xaa92a470,0xb05faa92,0xb16ab1a1,0x2f2d316a,0xaf2dad55,0xb0fdb1a1,0xb05fb0fd,0xad552470,0xb0fdb05f,0x2470ad55,0xad55af2d,0xb1a1b0fd,0xb1a1b16a,0x316a2f2d,0xa470aa92,0xaa92b05f,
0xae49a86a,0xb13aac54,0x2e49286a,0xb13aac54,0xb18cb0b4,0xac54b13a,0x318c30b4,0xac54b13a,0xb0b4b18c,0x313a2c54,0x30b4318c,0x313a2c54,0xa86aae49,0x2c54313a,0x286a2e49,0x2c54313a,
0xb1a1ad55,0xb0fdaf2d,0xa470b0fd,0xad55305f,0x2a92af2d,0x31a12a92,0x316a305f,0x2470b16a,0x305f316a,0xb16a2470,0xaf2d2a92,0x2a9231a1,0xb0fda470,0x305fad55,0xad55b1a1,0xaf2db0fd,
0xb18cae49,0xb000b000,0x318c2e49,0xb000b000,0x30b4a86a,0x30003000,0xb0b4286a,0x30003000,0xa86a30b4,0xb000b000,0x286ab0b4,0xb000b000,0xae49b18c,0x30003000,0x2e49318c,0x30003000,
0xad55b05f,0x2470b0fd,0x30fdaf2d,0xb1a12d55,0x2470316a,0xb16a305f,0xb1a12a92,0x2a922f2d,0x2a92b1a1,0x2f2d2a92,0x316a2470,0x305fb16a,0xaf2d30fd,0x2d55b1a1,0xb05fad55,0xb0fd2470,
0xa86ab0b4,0x2c54b13a,0x286a30b4,0x2c54b13a,0xae49318c,0xb13a2c54,0x2e49b18c,0xb13a2c54,0x318cae49,0xac54313a,0xb18c2e49,0xac54313a,0xb0b4a86a,0x313aac54,0x30b4286a,0x313aac54,
0x2f2db16a,0x316ab1a1,0x305faa92,0xaa922470,0xad55a470,0x305fb0fd,0x30fdb1a1,0xaf2d2d55,0xb1a130fd,0x2d55af2d,0xa470ad55,0xb0fd305f,0xaa92305f,0x2470aa92,0xb16a2f2d,0xb1a1316a,
0x30b4b18c,0x31a8b1a8,0xb0b4318c,0x31a8b1a8,0x286aae49,0x31a8b1a8,0xa86a2e49,0x31a8b1a8,0xae49286a,0x31a8b1a8,0x2e49a86a,0x31a8b1a8,0xb18c30b4,0x31a8b1a8,0x318cb0b4,0x31a8b1a8,
0x31a831a8,0x31a8,0x31a831a8,0x31a8,0x31a831a8,0x8000b1a8,0x31a831a8,0x8000b1a8,0x31a831a8,0x31a8,0x31a831a8,0x800031a8,0x31a831a8,0x8000b1a8,0x31a831a8,0x8000b1a8,
0x318c31a8,0xa86a31a8,0xa86a0000,0xb18c0000,0x30b4313a,0x2e49b13a,0xae49ac54,0x30b42c54,0x2e493000,0xb0b43000,0xb0b4b000,0xae49b000,0x286a2c54,0x318cac54,0xb18cb13a,0x286a313a,
0x313a31a8,0xac5431a8,0xb13ab1a8,0x2c54b1a8,0x2c543000,0x313ab000,0xac54b000,0xb13a3000,0xac540000,0xb13a0000,0x2c548000,0x313a8000,0xb13ab000,0x2c543000,0x313a3000,0xac54b000,
0x30b431a8,0xae4931a8,0x2e498000,0x30b48000,0xa86a2c54,0x318cac54,0x318c313a,0x286ab13a,0xb18cb000,0xa86ab000,0x286a3000,0xb18c3000,0xae49b13a,0xb0b4313a,0xb0b4ac54,0x2e492c54,
0x300031a8,0xb00031a8,0x300031a8,0xb00031a8,0xb0000000,0x30008000,0xb0000000,0x30008000,0xb000b1a8,0x3000b1a8,0xb000b1a8,0x3000b1a8,0x30008000,0xb0000000,0x30008000,0xb0008000,
0x2e4931a8,0xb0b431a8,0xb0b40000,0xae498000,0xb18cac54,0x286a2c54,0xa86ab13a,0xb18c313a,0x286ab000,0x318cb000,0x318c3000,0xa86a3000,0x30b4313a,0x2e49b13a,0xae492c54,0x30b4ac54,
0x2c5431a8,0xb13a31a8,0xac54b1a8,0x313ab1a8,0xb13ab000,0xac543000,0x313a3000,0x2c54b000,0x313a8000,0x2c548000,0xb13a0000,0xac548000,0xac543000,0x313ab000,0x2c54b000,0xb13a3000,
0x286a31a8,0xb18c31a8,0x318c8000,0x286a8000,0xae49b13a,0xb0b4313a,0xb0b42c54,0x2e49ac54,0x30b43000,0xae493000,0x2e49b000,0x30b4b000,0xb18cac54,0xa86a2c54,0xa86a313a,0x318cb13a,
0x800031a8,0xb1a831a8,0x80008000,0xb1a80000,0x80008000,0x31a88000,0x80008000,0x31a88000,0x80008000,0xb1a80000,0x80008000,0xb1a80000,0x80008000,0x31a88000,0x80008000,0x31a88000,
0xa86ab1a8,0xb18cb1a8,0xb18cb1a8,0x286ab1a8,0xae49ac54,0x30b42c54,0xb0b4b13a,0xae49313a,0xb0b4b000,0xae49b000,0xae49b000,0x30b4b000,0xb18cb13a,0x286a313a,0xa86aac54,0xb18c2c54,
0xac5431a8,0xb13a31a8,0x2c548000,0x313a8000,0xb13ab000,0x2c543000,0x313a3000,0xac54b000,0xb13ab1a8,0x2c54b1a8,0x313a31a8,0xac5431a8,0xac54b000,0xb13a3000,0x2c543000,0x313ab000,
0xae49b1a8,0xb0b4b1a8,0x30b431a8,0xae4931a8,0xb18cb13a,0xa86a313a,0xa86a2c54,0x318cac54,0xa86ab000,0x318cb000,0xb18cb000,0xa86ab000,0x30b42c54,0xae49ac54,0xae49b13a,0xb0b4313a,
0xb00031a8,0xb00031a8,0xb0000000,0xb0000000,0xb000b1a8,0xb00031a8,0xb000b1a8,0xb00031a8,0x30008000,0x30008000,0x30008000,0x30008000,0x300031a8,0x3000b1a8,0x300031a8,0x3000b1a8,
0xb0b4b1a8,0xae49b1a8,0xae49b1a8,0x30b4b1a8,0xa86ab13a,0xb18c313a,0x318c2c54,0xa86aac54,0x318c3000,0xa86a3000,0xa86a3000,0xb18c3000,0xae492c54,0x30b4ac54,0xb0b4b13a,0xae49313a,
0xb13a31a8,0xac5431a8,0x313a8000,0x2c548000,0x2c54b000,0xb13a3000,0xac543000,0x313ab000,0x2c5431a8,0xb13a31a8,0xac54b1a8,0x313ab1a8,0xb13ab000,0xac543000,0x313a3000,0x2c54b000,
0xb18cb1a8,0xa86ab1a8,0x286a31a8,0xb18c31a8,0x30b4ac54,0xae492c54,0xae49b13a,0xb0b4313a,0xae493000,0xb0b43000,0x30b43000,0xae493000,0x286ab13a,0xb18c313a,0xb18cac54,0xa86a2c54,
0xb1a831a8,0x800031a8,0xb1a831a8,0x800031a8,0xb1a831a8,0xb1a8,0xb1a831a8,0xb1a8,0xb1a831a8,0x800031a8,0xb1a831a8,0x800031a8,0xb1a831a8,0x8000b1a8,0xb1a831a8,0xb1a8,
0xb18c31a8,0x286a31a8,0x286a8000,0x318c8000,0xb0b4313a,0xae49b13a,0x2e49ac54,0xb0b42c54,0xae493000,0x30b43000,0x30b4b000,0x2e49b000,0xa86a2c54,0xb18cac54,0x318cb13a,0xa86a313a,
0xb13a31a8,0x2c5431a8,0x313ab1a8,0xac54b1a8,0xac543000,0xb13ab000,0x2c54b000,0x313a3000,0x2c540000,0x313a8000,0xac548000,0xb13a8000,0x313ab000,0xac543000,0xb13a3000,0x2c54b000,
0xb0b431a8,0x2e4931a8,0xae498000,0xb0b48000,0x286a2c54,0xb18cac54,0xb18c313a,0xa86ab13a,0x318cb000,0x286ab000,0xa86a3000,0x318c3000,0x2e49b13a,0x30b4313a,0x30b4ac54,0xae492c54,
0xb00031a8,0x300031a8,0xb00031a8,0x300031a8,0x30000000,0xb0008000,0x30008000,0xb0008000,0x3000b1a8,0xb000b1a8,0x3000b1a8,0xb000b1a8,0xb0008000,0x30008000,0xb0008000,0x30000000,
0xae4931a8,0x30b431a8,0x30b48000,0x2e498000,0x318cac54,0xa86a2c54,0x286ab13a,0x318c313a,0xa86ab000,0xb18cb000,0xb18c3000,0x286a3000,0xb0b4313a,0xae49b13a,0x2e492c54,0xb0b4ac54,
0xac5431a8,0x313a31a8,0x2c54b1a8,0xb13ab1a8,0x313ab000,0x2c543000,0xb13a3000,0xac54b000,0xb13a8000,0xac548000,0x313a0000,0x2c540000,0x2c543000,0xb13ab000,0xac54b000,0x313a3000,
0xa86a31a8,0x318c31a8,0xb18c8000,0xa86a8000,0x2e49b13a,0x30b4313a,0x30b42c54,0xae49ac54,0xb0b43000,0x2e493000,0xae49b000,0xb0b4b000,0x318cac54,0x286a2c54,0x286a313a,0xb18cb13a,
0x800031a8,0x31a831a8,0x80000000,0x31a80000,0x80000000,0xb1a88000,0x80000000,0xb1a88000,0x80000000,0x31a80000,0x0,0x31a80000,0x80000000,0xb1a88000,0x80000000,0xb1a80000,
0x286ab1a8,0x318cb1a8,0x318cb1a8,0xa86ab1a8,0x2e49ac54,0xb0b42c54,0x30b4b13a,0x2e49313a,0x30b4b000,0x2e49b000,0x2e49b000,0xb0b4b000,0x318cb13a,0xa86a313a,0x286aac54,0x318c2c54,
0x2c5431a8,0x313a31a8,0xac548000,0xb13a0000,0x313ab000,0xac543000,0xb13a3000,0x2c54b000,0x313ab1a8,0xac54b1a8,0xb13a31a8,0x2c5431a8,0x2c54b000,0x313a3000,0xac543000,0xb13ab000,
0x2e49b1a8,0x30b4b1a8,0xb0b431a8,0x2e4931a8,0x318cb13a,0x286a313a,0x286a2c54,0xb18cac54,0x286ab000,0xb18cb000,0x318cb000,0x286ab000,0xb0b42c54,0x2e49ac54,0x2e49b13a,0x30b4313a,
0x300031a8,0x300031a8,0x30000000,0x30000000,0x3000b1a8,0x300031a8,0x3000b1a8,0x300031a8,0xb0008000,0xb0008000,0xb0008000,0xb0000000,0xb00031a8,0xb000b1a8,0xb00031a8,0xb000b1a8,
0x30b4b1a8,0x2e49b1a8,0x2e49b1a8,0xb0b4b1a8,0x286ab13a,0x318c313a,0xb18c2c54,0x286aac54,0xb18c3000,0x286a3000,0x286a3000,0x318c3000,0x2e492c54,0xb0b4ac54,0x30b4b13a,0x2e49313a,
0x313a31a8,0x2c5431a8,0xb13a8000,0xac548000,0xac54b000,0x313a3000,0x2c543000,0xb13ab000,0xac5431a8,0x313a31a8,0x2c54b1a8,0xb13ab1a8,0x313ab000,0x2c543000,0xb13a3000,0xac54b000,
0x318cb1a8,0x286ab1a8,0xa86a31a8,0x318c31a8,0xb0b4ac54,0x2e492c54,0x2e49b13a,0x30b4313a,0x2e493000,0x30b43000,0xb0b43000,0x2e493000,0xa86ab13a,0x318c313a,0x318cac54,0x286a2c54,
};

__device__ __forceinline__ void wgmma_n256(float (&d)[128], uint64_t da, uint64_t db) {
  asm volatile("wgmma.mma_async.sync.aligned.m64n256k16.f32.bf16.bf16 {%0, %1, %2, %3, %4, %5, %6, %7, %8, %9, %10, %11, %12, %13, %14, %15, %16, %17, %18, %19, %20, %21, %22, %23, %24, %25, %26, %27, %28, %29, %30, %31, %32, %33, %34, %35, %36, %37, %38, %39, %40, %41, %42, %43, %44, %45, %46, %47, %48, %49, %50, %51, %52, %53, %54, %55, %56, %57, %58, %59, %60, %61, %62, %63, %64, %65, %66, %67, %68, %69, %70, %71, %72, %73, %74, %75, %76, %77, %78, %79, %80, %81, %82, %83, %84, %85, %86, %87, %88, %89, %90, %91, %92, %93, %94, %95, %96, %97, %98, %99, %100, %101, %102, %103, %104, %105, %106, %107, %108, %109, %110, %111, %112, %113, %114, %115, %116, %117, %118, %119, %120, %121, %122, %123, %124, %125, %126, %127}, %128, %129, 1, 1, 1, 0, 1;"
    : "+f"(d[0]), "+f"(d[1]), "+f"(d[2]), "+f"(d[3]), "+f"(d[4]), "+f"(d[5]), "+f"(d[6]), "+f"(d[7]), "+f"(d[8]), "+f"(d[9]), "+f"(d[10]), "+f"(d[11]), "+f"(d[12]), "+f"(d[13]), "+f"(d[14]), "+f"(d[15]), "+f"(d[16]), "+f"(d[17]), "+f"(d[18]), "+f"(d[19]), "+f"(d[20]), "+f"(d[21]), "+f"(d[22]), "+f"(d[23]), "+f"(d[24]), "+f"(d[25]), "+f"(d[26]), "+f"(d[27]), "+f"(d[28]), "+f"(d[29]), "+f"(d[30]), "+f"(d[31]), "+f"(d[32]), "+f"(d[33]), "+f"(d[34]), "+f"(d[35]), "+f"(d[36]), "+f"(d[37]), "+f"(d[38]), "+f"(d[39]), "+f"(d[40]), "+f"(d[41]), "+f"(d[42]), "+f"(d[43]), "+f"(d[44]), "+f"(d[45]), "+f"(d[46]), "+f"(d[47]), "+f"(d[48]), "+f"(d[49]), "+f"(d[50]), "+f"(d[51]), "+f"(d[52]), "+f"(d[53]), "+f"(d[54]), "+f"(d[55]), "+f"(d[56]), "+f"(d[57]), "+f"(d[58]), "+f"(d[59]), "+f"(d[60]), "+f"(d[61]), "+f"(d[62]), "+f"(d[63]), "+f"(d[64]), "+f"(d[65]), "+f"(d[66]), "+f"(d[67]), "+f"(d[68]), "+f"(d[69]), "+f"(d[70]), "+f"(d[71]), "+f"(d[72]), "+f"(d[73]), "+f"(d[74]), "+f"(d[75]), "+f"(d[76]), "+f"(d[77]), "+f"(d[78]), "+f"(d[79]), "+f"(d[80]), "+f"(d[81]), "+f"(d[82]), "+f"(d[83]), "+f"(d[84]), "+f"(d[85]), "+f"(d[86]), "+f"(d[87]), "+f"(d[88]), "+f"(d[89]), "+f"(d[90]), "+f"(d[91]), "+f"(d[92]), "+f"(d[93]), "+f"(d[94]), "+f"(d[95]), "+f"(d[96]), "+f"(d[97]), "+f"(d[98]), "+f"(d[99]), "+f"(d[100]), "+f"(d[101]), "+f"(d[102]), "+f"(d[103]), "+f"(d[104]), "+f"(d[105]), "+f"(d[106]), "+f"(d[107]), "+f"(d[108]), "+f"(d[109]), "+f"(d[110]), "+f"(d[111]), "+f"(d[112]), "+f"(d[113]), "+f"(d[114]), "+f"(d[115]), "+f"(d[116]), "+f"(d[117]), "+f"(d[118]), "+f"(d[119]), "+f"(d[120]), "+f"(d[121]), "+f"(d[122]), "+f"(d[123]), "+f"(d[124]), "+f"(d[125]), "+f"(d[126]), "+f"(d[127])
    : "l"(da), "l"(db));
}

__device__ __forceinline__ void wgmma_n256_first(float (&d)[128], uint64_t da, uint64_t db) {
  asm volatile("wgmma.mma_async.sync.aligned.m64n256k16.f32.bf16.bf16 {%0, %1, %2, %3, %4, %5, %6, %7, %8, %9, %10, %11, %12, %13, %14, %15, %16, %17, %18, %19, %20, %21, %22, %23, %24, %25, %26, %27, %28, %29, %30, %31, %32, %33, %34, %35, %36, %37, %38, %39, %40, %41, %42, %43, %44, %45, %46, %47, %48, %49, %50, %51, %52, %53, %54, %55, %56, %57, %58, %59, %60, %61, %62, %63, %64, %65, %66, %67, %68, %69, %70, %71, %72, %73, %74, %75, %76, %77, %78, %79, %80, %81, %82, %83, %84, %85, %86, %87, %88, %89, %90, %91, %92, %93, %94, %95, %96, %97, %98, %99, %100, %101, %102, %103, %104, %105, %106, %107, %108, %109, %110, %111, %112, %113, %114, %115, %116, %117, %118, %119, %120, %121, %122, %123, %124, %125, %126, %127}, %128, %129, 0, 1, 1, 0, 1;"
    : "=f"(d[0]), "=f"(d[1]), "=f"(d[2]), "=f"(d[3]), "=f"(d[4]), "=f"(d[5]), "=f"(d[6]), "=f"(d[7]), "=f"(d[8]), "=f"(d[9]), "=f"(d[10]), "=f"(d[11]), "=f"(d[12]), "=f"(d[13]), "=f"(d[14]), "=f"(d[15]), "=f"(d[16]), "=f"(d[17]), "=f"(d[18]), "=f"(d[19]), "=f"(d[20]), "=f"(d[21]), "=f"(d[22]), "=f"(d[23]), "=f"(d[24]), "=f"(d[25]), "=f"(d[26]), "=f"(d[27]), "=f"(d[28]), "=f"(d[29]), "=f"(d[30]), "=f"(d[31]), "=f"(d[32]), "=f"(d[33]), "=f"(d[34]), "=f"(d[35]), "=f"(d[36]), "=f"(d[37]), "=f"(d[38]), "=f"(d[39]), "=f"(d[40]), "=f"(d[41]), "=f"(d[42]), "=f"(d[43]), "=f"(d[44]), "=f"(d[45]), "=f"(d[46]), "=f"(d[47]), "=f"(d[48]), "=f"(d[49]), "=f"(d[50]), "=f"(d[51]), "=f"(d[52]), "=f"(d[53]), "=f"(d[54]), "=f"(d[55]), "=f"(d[56]), "=f"(d[57]), "=f"(d[58]), "=f"(d[59]), "=f"(d[60]), "=f"(d[61]), "=f"(d[62]), "=f"(d[63]), "=f"(d[64]), "=f"(d[65]), "=f"(d[66]), "=f"(d[67]), "=f"(d[68]), "=f"(d[69]), "=f"(d[70]), "=f"(d[71]), "=f"(d[72]), "=f"(d[73]), "=f"(d[74]), "=f"(d[75]), "=f"(d[76]), "=f"(d[77]), "=f"(d[78]), "=f"(d[79]), "=f"(d[80]), "=f"(d[81]), "=f"(d[82]), "=f"(d[83]), "=f"(d[84]), "=f"(d[85]), "=f"(d[86]), "=f"(d[87]), "=f"(d[88]), "=f"(d[89]), "=f"(d[90]), "=f"(d[91]), "=f"(d[92]), "=f"(d[93]), "=f"(d[94]), "=f"(d[95]), "=f"(d[96]), "=f"(d[97]), "=f"(d[98]), "=f"(d[99]), "=f"(d[100]), "=f"(d[101]), "=f"(d[102]), "=f"(d[103]), "=f"(d[104]), "=f"(d[105]), "=f"(d[106]), "=f"(d[107]), "=f"(d[108]), "=f"(d[109]), "=f"(d[110]), "=f"(d[111]), "=f"(d[112]), "=f"(d[113]), "=f"(d[114]), "=f"(d[115]), "=f"(d[116]), "=f"(d[117]), "=f"(d[118]), "=f"(d[119]), "=f"(d[120]), "=f"(d[121]), "=f"(d[122]), "=f"(d[123]), "=f"(d[124]), "=f"(d[125]), "=f"(d[126]), "=f"(d[127])
    : "l"(da), "l"(db));
}

typedef __nv_bfloat16 bf16;

constexpr int NSLOT = 528, VSLOT = 544;
__device__ __align__(1024) bf16 g_xn[2048 * 1024];
__device__ __align__(1024) bf16 g_h[2048 * 3584];
__device__ __align__(1024) bf16 g_s[2048 * 1024];
__device__ __align__(1024) uint4 g_V[2 * VSLOT * 256];
#define g_U g_V
__device__ __align__(128) float g_cs[7 * 16 * 256];
__device__ __align__(128) unsigned int g_st[2048];
constexpr int FL_LN = 0, FL_K1 = 1, FL_K2 = 2, FL_K3 = 3, FL_DONE = 4, FL_WM = 5, FL_WMAX = 6, FL_CS = 7, FL_H = 14, FL_COUNT = 14 + 64;
__device__ __align__(128) unsigned int g_flags[FL_COUNT * 32];

#define TS(idx)
#define TSW(w, idx)
constexpr int NCTA = 132, NG1 = 112, NFFT = 20;
constexpr uint32_t RING_BYTES = 196608, ST1 = 49152;
constexpr uint32_t STG_OFF = RING_BYTES, STG_STRIDE = 4240;
constexpr uint32_t WCOL = 4112, TAB2 = 52 * WCOL, VBUF = 68608, SOUT = 2 * VBUF, TAB3 = SOUT + 65536;
constexpr uint32_t BAR_OFF = STG_OFF + 8 * STG_STRIDE;
constexpr uint32_t WEXP_OFF = 400, CS_OFF = 640;
constexpr uint32_t SMEM_BYTES = BAR_OFF + 1664;
constexpr int N3J = 2;
constexpr int B_FULL = 0, B_EMPTY = 4,
              B_WMD = 9, B_CRDY = 10, B_UD = 11,
              B_LN = 12, B_K1ST = 13, B_H = 14, B_K2D = 14, B_K3D = 15, F_C3 = 16,
              B_HRDY = 18, B_SRDY = 22, B_GO = 23, B_XRDY = 24, B_URDY = 24, B_VGO = 25, B_WGO = 26, B_RAW = 27,
              F_VT = 28, F_TB = 30, B_WIN = 32, B_RAW2 = 33, B_XCH = 34;

__device__ __forceinline__ uint32_t smem_u32(const void* p) { return (uint32_t)__cvta_generic_to_shared(p); }
__device__ __forceinline__ void mbar_init(uint32_t bar, uint32_t count) { asm volatile("mbarrier.init.shared::cta.b64 [%0], %1;" ::"r"(bar), "r"(count) : "memory"); }
__device__ __forceinline__ void mbar_expect_tx(uint32_t bar, uint32_t bytes) { asm volatile("mbarrier.arrive.expect_tx.shared::cta.b64 _, [%0], %1;" ::"r"(bar), "r"(bytes) : "memory"); }
__device__ __forceinline__ void mbar_arrive(uint32_t bar) { asm volatile("mbarrier.arrive.shared::cta.b64 _, [%0];" ::"r"(bar) : "memory"); }
__device__ __forceinline__ void mbar_arrive_remote(uint32_t cluster_addr) { asm volatile("mbarrier.arrive.shared::cluster.b64 _, [%0];" ::"r"(cluster_addr) : "memory"); }
__device__ __forceinline__ uint32_t mapa(uint32_t addr, uint32_t cta) { uint32_t r; asm volatile("mapa.shared::cluster.u32 %0, %1, %2;" : "=r"(r) : "r"(addr), "r"(cta)); return r; }
__device__ __forceinline__ void mbar_wait(uint32_t bar, uint32_t parity) {
  asm volatile("{\n.reg .pred p;\n.reg .u32 c;\nmov.u32 c, 0;\n"
               "W_LOOP:\nmbarrier.try_wait.parity.shared::cta.b64 p, [%0], %1;\n@p bra W_DONE;\n"
               "add.u32 c, c, 1;\nsetp.lt.u32 p, c, 262144;\n@p bra W_LOOP;\nW_DONE:\n}\n" ::"r"(bar), "r"(parity) : "memory");
}
template <int SLEEP_NS>
__device__ __forceinline__ void wait_flag(const unsigned int* p, unsigned int target) {
  uint32_t it = 0;
#pragma unroll 1
  while (true) {
    unsigned int v;
    asm volatile("ld.relaxed.gpu.global.u32 %0, [%1];" : "=r"(v) : "l"(p) : "memory");
    if (v >= target || ++it > (1u << 18)) break;
    if (SLEEP_NS) __nanosleep(SLEEP_NS);
  }
  asm volatile("fence.acquire.gpu;" ::: "memory");
}
__device__ __forceinline__ void signal_flag(unsigned int* p) { asm volatile("red.release.gpu.global.add.u32 [%0], 1;" ::"l"(p) : "memory"); }
__device__ __forceinline__ void fence_proxy_async() { asm volatile("fence.proxy.async.global;" ::: "memory"); }
__device__ __forceinline__ void warp_arrive(uint32_t bar, int lane) { __syncwarp(); if (lane == 0) mbar_arrive(bar); }
__device__ __forceinline__ void tma_2d(uint32_t dst, const CUtensorMap* tm, int c0, int c1, uint32_t bar) {
  asm volatile("cp.async.bulk.tensor.2d.shared::cluster.global.mbarrier::complete_tx::bytes [%0], [%1, {%3, %4}], [%2];"
               ::"r"(dst), "l"(tm), "r"(bar), "r"(c0), "r"(c1) : "memory");
}
__device__ __forceinline__ void tma_3d_mc(uint32_t dst, const CUtensorMap* tm, int c1, int c2, uint32_t bar) {
  asm volatile("cp.async.bulk.tensor.3d.shared::cluster.global.mbarrier::complete_tx::bytes.multicast::cluster [%0], [%1, {%6, %3, %4}], [%2], %5;"
               ::"r"(dst), "l"(tm), "r"(bar), "r"(c1), "r"(c2), "h"((uint16_t)3), "r"(0) : "memory");
}
__device__ __forceinline__ void tma_3d(uint32_t dst, const CUtensorMap* tm, int c1, int c2, uint32_t bar) {
  asm volatile("cp.async.bulk.tensor.3d.shared::cluster.global.mbarrier::complete_tx::bytes [%0], [%1, {%5, %3, %4}], [%2];"
               ::"r"(dst), "l"(tm), "r"(bar), "r"(c1), "r"(c2), "r"(0) : "memory");
}
__device__ __forceinline__ void tma_5d(uint32_t dst, const CUtensorMap* tm, int c0, int c4, uint32_t bar) {
  asm volatile("cp.async.bulk.tensor.5d.shared::cluster.global.mbarrier::complete_tx::bytes [%0], [%1, {%3, %5, %5, %5, %4}], [%2];"
               ::"r"(dst), "l"(tm), "r"(bar), "r"(c0), "r"(c4), "r"(0) : "memory");
}
__device__ __forceinline__ void tma_store_2d(const CUtensorMap* tm, uint32_t src, int c0, int c1) {
  asm volatile("cp.async.bulk.tensor.2d.global.shared::cta.bulk_group [%0, {%2, %3}], [%1];" ::"l"(tm), "r"(src), "r"(c0), "r"(c1) : "memory");
}
__device__ __forceinline__ void bulk_g2s(uint32_t dst, const void* src, uint32_t bytes, uint32_t bar) {
  asm volatile("cp.async.bulk.shared::cluster.global.mbarrier::complete_tx::bytes [%0], [%1], %2, [%3];" ::"r"(dst), "l"(src), "r"(bytes), "r"(bar) : "memory");
}
__device__ __forceinline__ void bulk_s2g(void* dst, uint32_t src, uint32_t bytes) {
  asm volatile("cp.async.bulk.global.shared::cta.bulk_group [%0], [%1], %2;" ::"l"(dst), "r"(src), "r"(bytes) : "memory");
}
__device__ __forceinline__ void prefetch_tmap(const CUtensorMap* tm) { asm volatile("prefetch.tensormap [%0];" ::"l"(tm) : "memory"); }
__device__ __forceinline__ void wgmma_fence() { asm volatile("wgmma.fence.sync.aligned;" ::: "memory"); }
__device__ __forceinline__ void wgmma_commit() { asm volatile("wgmma.commit_group.sync.aligned;" ::: "memory"); }
template <int N> __device__ __forceinline__ void wgmma_wait() { asm volatile("wgmma.wait_group.sync.aligned %0;" ::"n"(N) : "memory"); }
__device__ __forceinline__ bool elect_one() {
  uint32_t p;
  asm volatile("{\n.reg .pred P;\nelect.sync _|P, 0xffffffff;\nselp.b32 %0, 1, 0, P;\n}\n" : "=r"(p));
  return p;
}
__device__ __forceinline__ void cluster_arrive() { asm volatile("barrier.cluster.arrive.relaxed.aligned;" ::: "memory"); }
__device__ __forceinline__ void cluster_wait() { asm volatile("barrier.cluster.wait.aligned;" ::: "memory"); }
template <int R> __device__ __forceinline__ void reg_inc() { asm volatile("setmaxnreg.inc.sync.aligned.u32 %0;" ::"n"(R)); }
template <int R> __device__ __forceinline__ void reg_dec() { asm volatile("setmaxnreg.dec.sync.aligned.u32 %0;" ::"n"(R)); }
__device__ __forceinline__ uint64_t make_desc(uint32_t addr, uint32_t lbo_bytes, uint32_t sbo_bytes) {
  return (uint64_t)((addr & 0x3FFFF) >> 4) | ((uint64_t)(lbo_bytes >> 4) << 16) | ((uint64_t)(sbo_bytes >> 4) << 32) | ((uint64_t)1 << 62);
}
__device__ __forceinline__ uint4 lds128(uint32_t a) { uint4 v; asm volatile("ld.shared.v4.u32 {%0,%1,%2,%3}, [%4];" : "=r"(v.x), "=r"(v.y), "=r"(v.z), "=r"(v.w) : "r"(a) : "memory"); return v; }
__device__ __forceinline__ uint32_t lds32(uint32_t a) { uint32_t v; asm volatile("ld.shared.u32 %0, [%1];" : "=r"(v) : "r"(a) : "memory"); return v; }
__device__ __forceinline__ uint2 lds64(uint32_t a) { uint2 v; asm volatile("ld.shared.v2.u32 {%0,%1}, [%2];" : "=r"(v.x), "=r"(v.y) : "r"(a) : "memory"); return v; }
__device__ __forceinline__ void sts32(uint32_t a, uint32_t x) { asm volatile("st.shared.u32 [%0], %1;" ::"r"(a), "r"(x) : "memory"); }
__device__ __forceinline__ void sts64(uint32_t a, uint32_t x, uint32_t y) { asm volatile("st.shared.v2.u32 [%0], {%1,%2};" ::"r"(a), "r"(x), "r"(y) : "memory"); }
__device__ __forceinline__ void sts128(uint32_t a, uint32_t x, uint32_t y, uint32_t z, uint32_t w) { asm volatile("st.shared.v4.u32 [%0], {%1,%2,%3,%4};" ::"r"(a), "r"(x), "r"(y), "r"(z), "r"(w) : "memory"); }
__device__ __forceinline__ uint4 ldtab(const uint4* tb, int row) { return __ldg(tb + row * 32); }
__device__ __forceinline__ uint4 ldts(uint32_t tb, int row) {
  uint4 v; asm("ld.shared.v4.u32 {%0,%1,%2,%3}, [%4];" : "=r"(v.x), "=r"(v.y), "=r"(v.z), "=r"(v.w) : "r"(tb + row * 512)); return v;
}
__device__ __forceinline__ uint32_t pack_f16(float lo, float hi) { uint32_t r; asm("cvt.rn.f16x2.f32 %0, %1, %2;" : "=r"(r) : "f"(hi), "f"(lo)); return r; }
__device__ __forceinline__ uint32_t pack_bf16(float lo, float hi) { uint32_t r; asm("cvt.rn.bf16x2.f32 %0, %1, %2;" : "=r"(r) : "f"(hi), "f"(lo)); return r; }
__device__ __forceinline__ float bf_lo(uint32_t v) { return __uint_as_float(v << 16); }
__device__ __forceinline__ float bf_hi(uint32_t v) { return __uint_as_float(v & 0xffff0000u); }
__device__ __forceinline__ float rnd_bf16(float v) { return __bfloat162float(__float2bfloat16_rn(v)); }
__device__ __forceinline__ void mma2h(uint32_t (&d)[2], const uint4& a0, const uint4& a1, uint32_t b0, uint32_t b1, uint32_t b2, uint32_t b3) {
  asm("mma.sync.aligned.m16n8k16.row.col.f16.f16.f16.f16 {%0,%1}, {%2,%3,%4,%5}, {%6,%7}, {%8,%8};"
      : "=r"(d[0]), "=r"(d[1]) : "r"(a0.x), "r"(a0.y), "r"(a0.z), "r"(a0.w), "r"(b0), "r"(b1), "r"(0u));
  asm("mma.sync.aligned.m16n8k16.row.col.f16.f16.f16.f16 {%0,%1}, {%2,%3,%4,%5}, {%6,%7}, {%0,%1};"
      : "+r"(d[0]), "+r"(d[1]) : "r"(a1.x), "r"(a1.y), "r"(a1.z), "r"(a1.w), "r"(b2), "r"(b3));
}
__device__ __forceinline__ void mma2f(float (&c)[4], const uint4& a0, const uint4& a1, uint32_t b0, uint32_t b1, uint32_t b2, uint32_t b3) {
  asm("mma.sync.aligned.m16n8k16.row.col.f32.f16.f16.f32 {%0,%1,%2,%3}, {%4,%5,%6,%7}, {%8,%9}, {%10,%10,%10,%10};"
      : "=f"(c[0]), "=f"(c[1]), "=f"(c[2]), "=f"(c[3]) : "r"(a0.x), "r"(a0.y), "r"(a0.z), "r"(a0.w), "r"(b0), "r"(b1), "f"(0.f));
  asm("mma.sync.aligned.m16n8k16.row.col.f32.f16.f16.f32 {%0,%1,%2,%3}, {%4,%5,%6,%7}, {%8,%9}, {%0,%1,%2,%3};"
      : "+f"(c[0]), "+f"(c[1]), "+f"(c[2]), "+f"(c[3]) : "r"(a1.x), "r"(a1.y), "r"(a1.z), "r"(a1.w), "r"(b2), "r"(b3));
}
__device__ __forceinline__ __half2 H(uint32_t v) { return *reinterpret_cast<__half2*>(&v); }
__device__ __forceinline__ uint32_t U(__half2 v) { return *reinterpret_cast<uint32_t*>(&v); }
__device__ __forceinline__ uint32_t hadd(uint32_t a, uint32_t b) { return U(__hadd2(H(a), H(b))); }
__device__ __forceinline__ uint32_t hsub(uint32_t a, uint32_t b) { return U(__hsub2(H(a), H(b))); }
__device__ __forceinline__ uint32_t hneg(uint32_t a) { return U(__hneg2(H(a))); }
__device__ __forceinline__ uint32_t hfma(uint32_t a, uint32_t b, uint32_t c) { return U(__hfma2(H(a), H(b), H(c))); }
__device__ __forceinline__ void cmul(uint32_t c, uint32_t s, uint32_t r, uint32_t i, uint32_t& pr, uint32_t& pi) {
  pr = U(__hfma2(H(r), H(c), __hneg2(__hmul2(H(i), H(s)))));
  pi = U(__hfma2(H(r), H(s), __hmul2(H(i), H(c))));
}
#define AFRAG(y, K) make_uint4(y[2 * (K)][0], y[2 * (K)][1], y[2 * (K) + 1][0], y[2 * (K) + 1][1])

__device__ __forceinline__ int k1_row(int chunk, int w) { return ((chunk >> 1) & 31) + 32 * (16 * (chunk >> 6) + 8 * (chunk & 1) + w); }

template <int P>
__device__ __forceinline__ void ln_piece(uint32_t (&pk)[64], int off, int lane, uint32_t bars, uint32_t src) {
  if (P == 0) {
    mbar_wait(bars + 8 * (B_RAW + (__shfl_sync(0xffffffffu, (int)(threadIdx.x >> 7), 0)) * (B_RAW2 - B_RAW)), 0);
#pragma unroll
    for (int i = 0; i < 16; ++i) { const uint2 v = lds64(src + i * 256); pk[2 * i] = v.x; pk[2 * i + 1] = v.y; }
    pk[36] = __shfl_sync(0xffffffffu, pk[0], 0) << 16; pk[39] = __shfl_sync(0xffffffffu, pk[16], 0) << 16;
  } else if (P == 10 || P == 11) {
    const int r = P - 10;
    const float c = __uint_as_float(pk[36 + 3 * r]);
    float s0 = 0.f, s1 = 0.f, q0 = 0.f, q1 = 0.f;
#pragma unroll
    for (int i = 0; i < 16; ++i) {
      const float d0 = bf_lo(pk[16 * r + i]) - c, d1 = bf_hi(pk[16 * r + i]) - c;
      s0 += d0; s1 += d1; q0 = fmaf(d0, d0, q0); q1 = fmaf(d1, d1, q1);
    }
    pk[34 + 3 * r] = __float_as_uint(s0 + s1); pk[35 + 3 * r] = __float_as_uint(q0 + q1);
  } else if (P == 8) {
    float v[4] = {__uint_as_float(pk[34]), __uint_as_float(pk[35]), __uint_as_float(pk[37]), __uint_as_float(pk[38])};
#pragma unroll
    for (int o = 16; o > 0; o >>= 1)
#pragma unroll
      for (int i = 0; i < 4; ++i) v[i] += __shfl_xor_sync(0xffffffffu, v[i], o);
    pk[34] = __float_as_uint(v[0]); pk[35] = __float_as_uint(v[1]); pk[37] = __float_as_uint(v[2]); pk[38] = __float_as_uint(v[3]);
  } else if (P == 9) {
#pragma unroll
    for (int r = 0; r < 2; ++r) {
      const float md = __uint_as_float(pk[34 + 3 * r]) * (1.f / 1024.f);
      const float var = fmaxf(fmaf(-md, md, __uint_as_float(pk[35 + 3 * r]) * (1.f / 1024.f)), 0.f);
      float sd, ri;
      asm("sqrt.approx.ftz.f32 %0, %1;" : "=f"(sd) : "f"(rnd_bf16(rnd_bf16(var) + 1e-5f)));
      pk[32 + r] = pack_bf16(__uint_as_float(pk[36 + 3 * r]) + md, sd);
      asm("rcp.approx.ftz.f32 %0, %1;" : "=f"(ri) : "f"(bf_hi(pk[32 + r])));
      pk[34 + 3 * r] = pack_bf16(ri, ri);
      const float rl = ri - bf_lo(pk[34 + 3 * r]);
      pk[35 + 3 * r] = pack_bf16(rl, rl);
    }
    if (lane < 2) g_st[(off >> 8) + lane * 1024] = lane ? pk[33] : pk[32];
  } else if (P == 2 || P == 3) {
    const int r = P - 2;
    uint2* xnp = reinterpret_cast<uint2*>(g_xn) + off + r * (1024 * 256);
    const uint32_t m2 = __byte_perm(pk[32 + r], 0, 0x1010);
    const uint32_t rh = pk[34 + 3 * r], rlo = pk[35 + 3 * r];
#pragma unroll
    for (int i = 0; i < 16; ++i) {
      asm("{\n.reg .b32 d, t;\nsub.rn.bf16x2 d, %0, %3;\nmul.rn.bf16x2 t, d, %2;\nfma.rn.bf16x2 %0, d, %1, t;\n}" : "+r"(pk[16 * r + i]) : "r"(rh), "r"(rlo), "r"(m2));
      if (i & 1) xnp[(i >> 1) * 32] = make_uint2(pk[16 * r + i - 1], pk[16 * r + i]);
    }
    if (P == 3) { warp_arrive(bars + 8 * B_LN, lane); TSW(4, 28); }
  } else {
    const int kh = P - 4;
#pragma unroll
    for (int J = 0; J < 4; ++J) {
      const uint32_t a0 = pk[4 * kh + (J >> 1)], a1 = pk[4 * kh + 2 + (J >> 1)], b0 = pk[16 + 4 * kh + (J >> 1)], b1 = pk[16 + 4 * kh + 2 + (J >> 1)];
      const float x0 = (J & 1) ? bf_hi(a0) : bf_lo(a0), x1 = (J & 1) ? bf_hi(a1) : bf_lo(a1), y0 = (J & 1) ? bf_hi(b0) : bf_lo(b0), y1 = (J & 1) ? bf_hi(b1) : bf_lo(b1);
      pk[32 + 4 * J + kh] = pack_f16(x0 + y0, x1 + y1);
      pk[48 + 4 * J + kh] = pack_f16(x0 - y0, x1 - y1);
    }
  }
}
__device__ __forceinline__ void k1_fft(const uint32_t (&b)[48], int w, int lane, uint32_t stg) {
  const int g = lane >> 2, q = lane & 3;
  const uint4* tb = reinterpret_cast<const uint4*>(g_tab) + lane;
  uint4 cA[4], cT[4], cB[4], cG[4];
#pragma unroll
  for (int i = 0; i < 4; ++i) { cA[i] = make_uint4(b[32 + 4 * i], b[33 + 4 * i], b[34 + 4 * i], b[35 + 4 * i]); cT[i] = ldtab(tb, TAB_T1 + i); cB[i] = ldtab(tb, TAB_B1 + i); cG[i] = ldtab(tb, TAB_G1 + i); }
  uint32_t PC[2][4][2], PS[2][4][2];
#pragma unroll
  for (int sg = 0; sg < 2; ++sg)
#pragma unroll
    for (int J = 0; J < 4; ++J) {
      const int o = 16 * sg + 4 * J;
      mma2h(PC[sg][J], cA[0], cA[1], b[o], b[o + 1], b[o + 2], b[o + 3]);
      mma2h(PS[sg][J], cA[2], cA[3], b[o], b[o + 1], b[o + 2], b[o + 3]);
    }
  const uint32_t reg = stg + w * STG_STRIDE;
  {
    const uint4 a0 = make_uint4(PS[0][0][0], PS[1][0][0], PS[0][1][0], PS[1][1][0]), a1 = make_uint4(PS[0][2][0], PS[1][2][0], PS[0][3][0], PS[1][3][0]);
    uint32_t Dm[4][2];
#pragma unroll
    for (int j = 0; j < 4; ++j) mma2h(Dm[j], a0, a1, cG[j].x, cG[j].y, cG[j].z, cG[j].w);
    if (g == 0) {
#pragma unroll
      for (int sg = 0; sg < 2; ++sg)
#pragma unroll
        for (int j = 0; j < 2; ++j) sts64(reg + (sg * NSLOT + 512 + 8 * j + 2 * q) * 4, Dm[j][sg], Dm[j + 2][sg]);
    }
  }
  const uint32_t msk = (g == 0) ? 0u : 0xffffffffu;
#pragma unroll
  for (int sg = 0; sg < 2; ++sg) {
    uint32_t yr[4][2], yi[4][2];
#pragma unroll
    for (int J = 0; J < 4; ++J) {
      cmul(cT[J].x, cT[J].y, PC[sg][J][0], PS[sg][J][0] & msk, yr[J][0], yi[J][0]);
      cmul(cT[J].z, cT[J].w, PC[sg][J][1], PS[sg][J][1], yr[J][1], yi[J][1]);
    }
    uint32_t Pm[4][2], Qm[4][2];
#pragma unroll
    for (int j = 0; j < 4; ++j) {
      mma2h(Pm[j], AFRAG(yr, 0), AFRAG(yr, 1), cB[j].x, cB[j].y, cB[j].z, cB[j].w);
      mma2h(Qm[j], AFRAG(yi, 0), AFRAG(yi, 1), cB[j].x, cB[j].y, cB[j].z, cB[j].w);
    }
#pragma unroll
    for (int j = 0; j < 2; ++j)
#pragma unroll
      for (int hh = 0; hh < 2; ++hh) {
        const uint32_t rowb = reg + (sg * NSLOT + (g + 8 * hh) * 32 + 2 * q) * 4;
        sts64(rowb + ((j ^ (g & 3)) << 5), hadd(Pm[j][hh], Qm[j + 2][hh]), hsub(Qm[j][hh], Pm[j + 2][hh]));
        sts64(rowb + (((j + 2) ^ (g & 3)) << 5), hsub(Pm[j][hh], Qm[j + 2][hh]), hsub(hneg(Qm[j][hh]), Pm[j + 2][hh]));
      }
  }
}

__device__ __forceinline__ int slot_of_col(int col) {
  const int lo = col & 31, c = col >> 5;
  if (col == 512) return 31;
  if (lo < 16) return lo * 32 + c;
  if (lo == 16) return 512 + c;
  return (32 - lo) * 32 + 16 + c;
}

__device__ __forceinline__ void k2_load(int sg, int slot, int lane, uint32_t (&u)[32]) {
  const uint4* up = g_U + (size_t)(sg * VSLOT + slot) * 256 + lane;
#pragma unroll
  for (int i = 0; i < 8; ++i) { const uint4 a = __ldcg(up + i * 32); u[4 * i] = a.x; u[4 * i + 1] = a.y; u[4 * i + 2] = a.z; u[4 * i + 3] = a.w; }
}
__device__ __forceinline__ void k2_task(int sg, int slot, int lane, uint32_t wreg, uint32_t tb, const uint32_t (&u)[32]) {
  const int g = lane >> 2;
  uint32_t yr[2][4][2], yi[2][4][2];
  {
    uint4 c[4];
#pragma unroll
    for (int i = 0; i < 4; ++i) c[i] = ldts(tb, TAB_A2_0 + i - TAB_B2);
    const uint32_t lam = (g == 0 && sg == 0) ? 0u : 0x3c003c00u;
#pragma unroll
    for (int J = 0; J < 4; ++J) {
      uint32_t P1[2], P2[2], P3[2], P4[2];
      mma2h(P1, c[0], c[1], u[4 * J], u[4 * J + 1], u[16 + 4 * J], u[16 + 4 * J + 1]);
      mma2h(P2, c[2], c[3], u[4 * J + 2], u[4 * J + 3], u[16 + 4 * J + 2], u[16 + 4 * J + 3]);
      mma2h(P3, c[0], c[1], u[4 * J + 2], u[4 * J + 3], u[16 + 4 * J + 2], u[16 + 4 * J + 3]);
      mma2h(P4, c[2], c[3], u[4 * J], u[4 * J + 1], u[16 + 4 * J], u[16 + 4 * J + 1]);
      const uint4 tp_ = ldts(tb, TAB_T2_0 + J - TAB_B2), tm_ = ldts(tb, TAB_T2_0 + 4 + J - TAB_B2);
      cmul(tp_.x, tp_.y, hfma(lam, P2[0], P1[0]), hfma(lam, hneg(P4[0]), P3[0]), yr[0][J][0], yi[0][J][0]);
      cmul(tp_.z, tp_.w, hadd(P1[1], P2[1]), hsub(P3[1], P4[1]), yr[0][J][1], yi[0][J][1]);
      cmul(tm_.x, tm_.y, hfma(lam, P1[0], hneg(P2[0])), hfma(lam, P3[0], P4[0]), yr[1][J][0], yi[1][J][0]);
      cmul(tm_.z, tm_.w, hsub(P1[1], P2[1]), hadd(P3[1], P4[1]), yr[1][J][1], yi[1][J][1]);
    }
  }
  uint32_t zr[2][4][2], zi[2][4][2];
  {
    uint4 c[4];
#pragma unroll
    for (int i = 0; i < 4; ++i) c[i] = ldts(tb, TAB_B2 + i - TAB_B2);
#pragma unroll
    for (int M = 0; M < 2; ++M) {
#pragma unroll
      for (int j = 0; j < 2; ++j) {
        uint32_t PC[2], PS[2], QC[2], QS[2];
        mma2h(PC, AFRAG(yr[M], 0), AFRAG(yr[M], 1), c[j].x, c[j].y, c[j].z, c[j].w);
        mma2h(QS, AFRAG(yi[M], 0), AFRAG(yi[M], 1), c[j + 2].x, c[j + 2].y, c[j + 2].z, c[j + 2].w);
        mma2h(QC, AFRAG(yi[M], 0), AFRAG(yi[M], 1), c[j].x, c[j].y, c[j].z, c[j].w);
        mma2h(PS, AFRAG(yr[M], 0), AFRAG(yr[M], 1), c[j + 2].x, c[j + 2].y, c[j + 2].z, c[j + 2].w);
        const uint4 wp = lds128(wreg + ((M * 4 + j) * 32 + lane) * 16), wm = lds128(wreg + ((M * 4 + j + 2) * 32 + lane) * 16);
        cmul(wp.x, wp.y, hadd(PC[0], QS[0]), hsub(QC[0], PS[0]), zr[M][j][0], zi[M][j][0]);
        cmul(wp.z, wp.w, hadd(PC[1], QS[1]), hsub(QC[1], PS[1]), zr[M][j][1], zi[M][j][1]);
        cmul(wm.x, wm.y, hsub(PC[0], QS[0]), hadd(QC[0], PS[0]), zr[M][j + 2][0], zi[M][j + 2][0]);
        cmul(wm.z, wm.w, hsub(PC[1], QS[1]), hadd(QC[1], PS[1]), zr[M][j + 2][1], zi[M][j + 2][1]);
      }
    }
  }
  {
    uint4 c[4];
#pragma unroll
    for (int i = 0; i < 4; ++i) c[i] = ldts(tb, TAB_A3 + i - TAB_B2);
#pragma unroll
    for (int J = 0; J < 4; ++J) {
      const int M = J >> 1, hh = J & 1;
      uint32_t P1[2], P2[2], P3[2], P4[2];
      mma2h(P1, c[0], c[1], zr[M][0][hh], zr[M][1][hh], zr[M][2][hh], zr[M][3][hh]);
      mma2h(P2, c[2], c[3], zi[M][0][hh], zi[M][1][hh], zi[M][2][hh], zi[M][3][hh]);
      mma2h(P3, c[0], c[1], zi[M][0][hh], zi[M][1][hh], zi[M][2][hh], zi[M][3][hh]);
      mma2h(P4, c[2], c[3], zr[M][0][hh], zr[M][1][hh], zr[M][2][hh], zr[M][3][hh]);
      const uint4 tp_ = ldts(tb, TAB_T3_0 + J - TAB_B2), tm_ = ldts(tb, TAB_T3_0 + 4 + J - TAB_B2);
      cmul(tp_.x, tp_.y, hsub(P1[0], P2[0]), hadd(P3[0], P4[0]), yr[0][J][0], yi[0][J][0]);
      cmul(tp_.z, tp_.w, hsub(P1[1], P2[1]), hadd(P3[1], P4[1]), yr[0][J][1], yi[0][J][1]);
      cmul(tm_.x, tm_.y, hadd(P1[0], P2[0]), hsub(P3[0], P4[0]), yr[1][J][0], yi[1][J][0]);
      cmul(tm_.z, tm_.w, hadd(P1[1], P2[1]), hsub(P3[1], P4[1]), yr[1][J][1], yi[1][J][1]);
    }
  }
  {
    uint4 c[4];
#pragma unroll
    for (int i = 0; i < 4; ++i) c[i] = ldts(tb, TAB_B4_0 + i - TAB_B2);
    uint4* vp = g_V + (size_t)(sg * VSLOT + slot) * 256 + lane;
#pragma unroll
    for (int M = 0; M < 2; ++M) {
#pragma unroll
      for (int j = 0; j < 2; ++j) {
        uint32_t PC[2], PS[2], QC[2], QS[2];
        mma2h(PC, AFRAG(yr[M], 0), AFRAG(yr[M], 1), c[j].x, c[j].y, c[j].z, c[j].w);
        mma2h(QS, AFRAG(yi[M], 0), AFRAG(yi[M], 1), c[j + 2].x, c[j + 2].y, c[j + 2].z, c[j + 2].w);
        mma2h(QC, AFRAG(yi[M], 0), AFRAG(yi[M], 1), c[j].x, c[j].y, c[j].z, c[j].w);
        mma2h(PS, AFRAG(yr[M], 0), AFRAG(yr[M], 1), c[j + 2].x, c[j + 2].y, c[j + 2].z, c[j + 2].w);
        vp[(j * 2 + M) * 32] = make_uint4(hsub(PC[0], QS[0]), hadd(QC[0], PS[0]), hsub(PC[1], QS[1]), hadd(QC[1], PS[1]));
        vp[((j + 2) * 2 + M) * 32] = make_uint4(hadd(PC[0], QS[0]), hsub(QC[0], PS[0]), hadd(PC[1], QS[1]), hsub(QC[1], PS[1]));
      }
    }
  }
}

__device__ __forceinline__ void k3_task(int chunk, int el, int lane, const uint4 (&d)[9], uint32_t out, uint32_t tb, float sc) {
  const int g = lane >> 2, q = lane & 3;
  uint32_t E[2][2];
  mma2h(E[0], ldts(tb, TAB_A6 - TAB_A5), ldts(tb, TAB_A6 + 1 - TAB_A5), d[8].x, d[8].y, d[8].z, d[8].w);
  mma2h(E[1], ldts(tb, TAB_A6 + 2 - TAB_A5), ldts(tb, TAB_A6 + 3 - TAB_A5), d[8].x, d[8].y, d[8].z, d[8].w);
  uint4 c[6], tw[4], a7[4];
#pragma unroll
  for (int i = 0; i < 6; ++i) c[i] = ldts(tb, TAB_A5 + i - TAB_A5);
#pragma unroll
  for (int i = 0; i < 4; ++i) tw[i] = ldts(tb, TAB_T5 + i - TAB_A5);
#pragma unroll
  for (int i = 0; i < 4; ++i) a7[i] = ldts(tb, TAB_A7 + i - TAB_A5);
  float t[2][2][4][4];
#pragma unroll
  for (int sg = 0; sg < 2; ++sg) {
    uint32_t ur[2][2][2], ui[2][2][2];
#pragma unroll
    for (int Jn = 0; Jn < 2; ++Jn) {
      const uint4 d0 = d[sg * 4 + Jn * 2], d1 = d[sg * 4 + Jn * 2 + 1];
      uint32_t P1[2], P2[2], P3[2], P4[2];
      mma2h(P1, c[0], c[1], d0.x, d0.y, d1.x, d1.y);
      mma2h(P2, c[2], c[5], d0.z, d0.w, d1.z, d1.w);
      mma2h(P3, c[0], c[4], d0.z, d0.w, d1.z, d1.w);
      mma2h(P4, c[2], c[3], d0.x, d0.y, d1.x, d1.y);
      cmul(tw[Jn].x, tw[Jn].y, hsub(P1[0], P2[0]), hadd(P3[0], P4[0]), ur[0][Jn][0], ui[0][Jn][0]);
      cmul(tw[Jn].z, tw[Jn].w, hsub(P1[1], P2[1]), hadd(P3[1], P4[1]), ur[0][Jn][1], ui[0][Jn][1]);
      cmul(tw[2 + Jn].x, tw[2 + Jn].y, hadd(P1[0], P2[0]), hsub(P3[0], P4[0]), ur[1][Jn][0], ui[1][Jn][0]);
      cmul(tw[2 + Jn].z, tw[2 + Jn].w, hadd(P1[1], P2[1]), hsub(P3[1], P4[1]), ur[1][Jn][1], ui[1][Jn][1]);
    }
    const uint32_t sel = q ? 0x7654u : (sg ? 0x7632u : 0x7610u);
#pragma unroll
    for (int nt = 0; nt < 4; ++nt) ui[nt >> 1][0][nt & 1] = __byte_perm(E[nt >> 1][nt & 1], ui[nt >> 1][0][nt & 1], sel);
#pragma unroll
    for (int Mt = 0; Mt < 2; ++Mt)
#pragma unroll
      for (int nt = 0; nt < 4; ++nt)
        mma2f(t[sg][Mt][nt], a7[2 * Mt], a7[2 * Mt + 1], ur[nt >> 1][0][nt & 1], ur[nt >> 1][1][nt & 1], ui[nt >> 1][0][nt & 1], ui[nt >> 1][1][nt & 1]);
  }
  const int cj = chunk >> 5, r = 8 * ((el >> 1) & 1) + ((chunk >> 1) & 7), sp = (chunk & 16) ? -r - 1 : r;
  const int cc = 8 * (cj & 1) + 4 * (chunk & 1) + 2 * (el >> 2) + (el & 1), sh = (cj < 2) ? cc : -cc - 1;
  const int p = sp + 32 * sh;
  const uint32_t sa = out + g * 64 + q * 8, sb = out + g * 64 + (7 - q) * 8;
#pragma unroll
  for (int Mt = 0; Mt < 2; ++Mt)
#pragma unroll
    for (int h2 = 0; h2 < 2; ++h2) {
      const int o = (16 * Mt + 8 * h2) * 64, i0 = 2 * h2, i1 = 2 * h2 + 1;
      float ev[4][2], od[4][2];
#pragma unroll
      for (int nt = 0; nt < 4; ++nt) {
        const float a0 = t[0][Mt][nt][i0] * sc, a1 = t[0][Mt][nt][i1] * sc;
        ev[nt][0] = fmaf(t[1][Mt][nt][i0], sc, a0); od[nt][0] = fmaf(t[1][Mt][nt][i0], -sc, a0);
        ev[nt][1] = fmaf(t[1][Mt][nt][i1], sc, a1); od[nt][1] = fmaf(t[1][Mt][nt][i1], -sc, a1);
      }
      sts64(sa + o, pack_bf16(ev[0][0], ev[0][1]), pack_bf16(ev[1][0], ev[1][1]));
      sts64(sb + o, pack_bf16(ev[3][1], ev[3][0]), pack_bf16(ev[2][1], ev[2][0]));
      sts64(sa + o + 2048, pack_bf16(od[0][0], od[0][1]), pack_bf16(od[1][0], od[1][1]));
      sts64(sb + o + 2048, pack_bf16(od[3][1], od[3][0]), pack_bf16(od[2][1], od[2][0]));
    }
  asm volatile("fence.proxy.async.shared::cta;" ::: "memory");
  __syncwarp();
  if (elect_one()) {
    bulk_s2g(g_s + (size_t)(p & 2047) * 1024, out, 2048);
    bulk_s2g(g_s + (size_t)((p + 1024) & 2047) * 1024, out + 2048, 2048);
    asm volatile("cp.async.bulk.commit_group;" ::: "memory");
  }
}

__device__ __forceinline__ void u_copy(int chunk, int ht, uint32_t stg) {
  const uint32_t sb = stg + (ht & 1) * (4 * STG_STRIDE);
  uint4* dst = g_U + chunk * 2 + (ht & 1);
#pragma unroll 3
  for (int it = ht >> 1; it < NSLOT; it += 32) {
    const int pr = it >= NSLOT / 2 ? it - NSLOT / 2 : it;
    const uint32_t a = sb + (it - pr + (pr < 256 ? (pr ^ (((pr >> 4) & 3) << 2)) : pr)) * 8;
    const uint2 v0 = lds64(a), v1 = lds64(a + STG_STRIDE), v2 = lds64(a + 2 * STG_STRIDE), v3 = lds64(a + 3 * STG_STRIDE);
    const size_t go = (size_t)(it == pr ? it : pr + VSLOT / 2) * 512;
    dst[go] = make_uint4(__byte_perm(v0.x, v1.x, 0x5410), __byte_perm(v2.x, v3.x, 0x5410), __byte_perm(v0.y, v1.y, 0x5410), __byte_perm(v2.y, v3.y, 0x5410));
    dst[go + 256] = make_uint4(__byte_perm(v0.x, v1.x, 0x7632), __byte_perm(v2.x, v3.x, 0x7632), __byte_perm(v0.y, v1.y, 0x7632), __byte_perm(v2.y, v3.y, 0x7632));
  }
}

__device__ __forceinline__ void cs_partial(const bf16* __restrict__ wmat, int mblk1, int ngrp1, int ht) {
  const int lane = ht & 31;
  const uint4* p = reinterpret_cast<const uint4*>(wmat + (size_t)(mblk1 * 64 + (lane >> 4)) * 3584 + ngrp1 * 128) + (lane & 15);
  float s[8];
#pragma unroll
  for (int i = 0; i < 8; ++i) s[i] = 0.f;
#pragma unroll 1
  for (int bt = 0; bt < 4; ++bt) {
    uint4 v[8];
#pragma unroll
    for (int i = 0; i < 8; ++i) v[i] = __ldg(p + (bt * 8 + i) * (2 * 448));
#pragma unroll
    for (int i = 0; i < 8; ++i) {
      s[0] += bf_lo(v[i].x); s[1] += bf_hi(v[i].x); s[2] += bf_lo(v[i].y); s[3] += bf_hi(v[i].y);
      s[4] += bf_lo(v[i].z); s[5] += bf_hi(v[i].z); s[6] += bf_lo(v[i].w); s[7] += bf_hi(v[i].w);
    }
  }
#pragma unroll
  for (int i = 0; i < 8; ++i) s[i] += __shfl_xor_sync(0xffffffffu, s[i], 16);
  if (lane < 16) {
    float4* d = reinterpret_cast<float4*>(g_cs + (ngrp1 * 16 + mblk1) * 256 + (ht >> 5) * 128 + lane * 8);
    d[0] = make_float4(s[0], s[1], s[2], s[3]); d[1] = make_float4(s[4], s[5], s[6], s[7]);
  }
}
__device__ __forceinline__ void cs_total(int ngrp1, int ht, uint32_t dst) {
  const float4* p = reinterpret_cast<const float4*>(g_cs + ngrp1 * 4096) + ht;
  float s[4] = {0.f, 0.f, 0.f, 0.f};
#pragma unroll 1
  for (int hf = 0; hf < 2; ++hf) {
    float4 v[8];
#pragma unroll
    for (int i = 0; i < 8; ++i) v[i] = __ldcg(p + (hf * 8 + i) * 64);
#pragma unroll
    for (int i = 0; i < 8; ++i) { s[0] += v[i].x; s[1] += v[i].y; s[2] += v[i].z; s[3] += v[i].w; }
  }
  const uint32_t a = dst + (ht >> 2) * 64 + (ht & 1) * 32 + ((ht >> 1) & 1) * 8;
  sts64(a, __float_as_uint(s[0]), __float_as_uint(s[1]));
  sts64(a + 16, __float_as_uint(s[2]), __float_as_uint(s[3]));
}
__device__ __forceinline__ void w_max(const uint4* __restrict__ p, uint32_t sm, uint32_t bar, int tid) {
  uint4 v[4];
#pragma unroll
  for (int i = 0; i < 4; ++i) v[i] = __ldg(p + 12288 + i * 256 + tid);
  mbar_wait(bar, 0);
  uint32_t m = 0;
#pragma unroll 1
  for (int bt = 0; bt < 13; ++bt) {
#pragma unroll
    for (int i = 0; i < 4; ++i)
      m = __vmaxu2(__vmaxu2(m, __vmaxu2(v[i].x & 0x7fff7fffu, v[i].y & 0x7fff7fffu)), __vmaxu2(v[i].z & 0x7fff7fffu, v[i].w & 0x7fff7fffu));
    if (bt < 12) {
#pragma unroll
      for (int i = 0; i < 4; ++i) v[i] = lds128(sm + bt * 16384 + i * 4096 + tid * 16);
    }
  }
  m = __reduce_max_sync(0xffffffffu, max(m & 0xffffu, m >> 16));
  if ((tid & 31) == 0) asm volatile("red.relaxed.gpu.global.max.u32 [%0], %1;" ::"l"(&g_flags[FL_WMAX * 32]), "r"(m) : "memory");
}

__device__ __forceinline__ void w_fetch(const unsigned short* __restrict__ wr, const unsigned short* __restrict__ wi, int sg, int col, int warp, int g0, uint32_t (&a)[2][2][8], uint32_t (&c)[2][2][8]) {
  const int M = warp >> 2, jt = warp & 3;
  const int mh0 = jt < 2 ? 8 * jt : 15 - 8 * jt, step = jt < 2 ? 64 : -64;
#pragma unroll
  for (int g = 0; g < 2; ++g)
#pragma unroll
    for (int hh = 0; hh < 2; ++hh) {
      int kap = 2 * (g0 + g + 8 * hh) + sg;
      if (M) kap = kap ? -kap : 32;
      kap += 64 * mh0;
#pragma unroll
      for (int i = 0; i < 8; ++i) {
        const int o = ((kap + step * i) & 2047) * 513 + col;
        asm volatile("ld.global.nc.u32 %0, [%1];" : "=r"(a[g][hh][i]) : "l"(wr + o));
        asm volatile("ld.global.nc.u32 %0, [%1];" : "=r"(c[g][hh][i]) : "l"(wi + o));
      }
    }
}
__device__ __forceinline__ void w_store(int col, uint32_t dst, float sc, const uint32_t (&a)[2][2][8], const uint32_t (&c)[2][2][8]) {
  const float s0 = (col & 511) == 0 ? 0.5f * sc : sc, s1 = ((col + 1) & 511) == 0 ? 0.5f * sc : sc;
#pragma unroll
  for (int g = 0; g < 2; ++g)
#pragma unroll
    for (int q = 0; q < 4; ++q) {
      const int i = 2 * q;
      sts128(dst + (g * 4 + q) * 16, pack_f16(bf_lo(a[g][0][i]) * s0, bf_lo(a[g][0][i + 1]) * s0), pack_f16(bf_lo(c[g][0][i]) * s0, bf_lo(c[g][0][i + 1]) * s0),
             pack_f16(bf_lo(a[g][1][i]) * s0, bf_lo(a[g][1][i + 1]) * s0), pack_f16(bf_lo(c[g][1][i]) * s0, bf_lo(c[g][1][i + 1]) * s0));
      sts128(dst + WCOL + (g * 4 + q) * 16, pack_f16(bf_hi(a[g][0][i]) * s1, bf_hi(a[g][0][i + 1]) * s1), pack_f16(bf_hi(c[g][0][i]) * s1, bf_hi(c[g][0][i + 1]) * s1),
             pack_f16(bf_hi(a[g][1][i]) * s1, bf_hi(a[g][1][i + 1]) * s1), pack_f16(bf_hi(c[g][1][i]) * s1, bf_hi(c[g][1][i + 1]) * s1));
    }
}

__device__ __forceinline__ float swiglu(float gt, float up) {
  const float hg = 0.5f * gt, a = hg * (0.5f * up);
  float t;
  asm("tanh.approx.f32 %0, %1;" : "=f"(t) : "f"(hg));
  return fmaf(a, t, a);
}
__device__ __forceinline__ uint32_t swiglu2(uint32_t g2, uint32_t u2) { return pack_bf16(swiglu(bf_lo(g2), bf_lo(u2)), swiglu(bf_hi(g2), bf_hi(u2))); }
__device__ __forceinline__ void epi_chunk(const uint32_t (&pk)[64], int c, bf16* dst) {
  uint4 o;
  o.x = swiglu2(pk[8 * c + 0], pk[8 * c + 4]);
  o.y = swiglu2(pk[8 * c + 1], pk[8 * c + 5]);
  o.z = swiglu2(pk[8 * c + 2], pk[8 * c + 6]);
  o.w = swiglu2(pk[8 * c + 3], pk[8 * c + 7]);
  *reinterpret_cast<uint4*>(dst + (c & 1) * (8 * 3584) + (c >> 1) * 32) = o;
}
template <int NJ, int J0, int JN = 8>
__device__ __forceinline__ void pack_acc(const float (&acc)[8 * NJ], uint32_t (&pk)[64]) {
#pragma unroll
  for (int j = J0; j < J0 + JN; ++j)
#pragma unroll
    for (int hh = 0; hh < 2; ++hh) {
      const int c = (j >> 2) * 2 + hh;
      pk[8 * c + (j & 3)] = pack_bf16(acc[4 * j + 2 * hh], acc[4 * j + 2 * hh + 1]);
      pk[8 * c + 4 + (j & 3)] = pack_bf16(acc[4 * (j + NJ) + 2 * hh], acc[4 * (j + NJ) + 2 * hh + 1]);
    }
}

__device__ __forceinline__ int g2_block(int i, int kh) { return i + 7 * (kh + (i >= 7) + (i >= 14) + (i >= 21)); }

__device__ __forceinline__ void ln_fix(float (&acc)[128], int pc, uint32_t cs, float m0, float m1, float r0, float r1) {
#pragma unroll
  for (int jp = 4 * pc; jp < 4 * pc + 4; ++jp) {
    const uint4 c = lds128(cs + jp * 64);
    const float cf[4] = {__uint_as_float(c.x), __uint_as_float(c.y), __uint_as_float(c.z), __uint_as_float(c.w)};
#pragma unroll
    for (int i = 0; i < 4; ++i) {
      const int o = 8 * jp + (i >> 1) * 4 + (i & 1);
      asm volatile("fma.rn.f32 %0, %1, %2, %0;\nmul.rn.f32 %0, %0, %3;" : "+f"(acc[o]) : "f"(m0), "f"(cf[i]), "f"(r0));
      asm volatile("fma.rn.f32 %0, %1, %2, %0;\nmul.rn.f32 %0, %0, %3;" : "+f"(acc[o + 2]) : "f"(m1), "f"(cf[i]), "f"(r1));
    }
  }
}

#define SCHED_FENCE mbar_wait(bars + 8 * B_SRDY, 1)

struct Maps { CUtensorMap xn, wgu3[2], h, wd, x, s, out, v, v16; };

__global__ void __cluster_dims__(2, 1, 1) __launch_bounds__(384, 1)
fused_kernel(const __grid_constant__ Maps maps, const bf16* __restrict__ x, const unsigned short* __restrict__ wr, const unsigned short* __restrict__ wi,
             const bf16* __restrict__ wgate, const bf16* __restrict__ wup, const uint32_t zero) {
  extern __shared__ __align__(1024) uint8_t smem_raw[];
  const uint32_t sbase = smem_u32(smem_raw);
  if (sbase & 1023) return;
  const uint32_t stg = sbase + STG_OFF, bars = sbase + BAR_OFF;
  const int tid = threadIdx.x, lane = tid & 31;
#define UWARP __shfl_sync(0xffffffffu, (int)(threadIdx.x >> 5), 0)
  const int rank = blockIdx.x & 1, bc = blockIdx.x >> 1, c7 = (bc - 36) % 7;
  const int gg = bc < 4 ? 0 : bc < 36 ? (bc + 3) & 7 : c7 ? c7 : 7, gi = bc < 4 ? 4 + bc : bc < 36 ? (bc - 4) >> 3 : 4 + (bc - 36) / 7;
  const int cl = bc < 64 ? gi * 8 + gg : bc, cta = 2 * cl + rank;
  const bool is_fft = cta >= NG1;
  const int fi = cta - NG1;
  const int mblk1 = 2 * (cl & 7) + rank, ngrp1 = cl >> 3;
  const int mblk = (gg >> 1) * 4 + (gi & 3), ngrp = (((gg & 1) * 2 + (gi >> 2)) & 3) * 2 + rank;
  const int n3 = fi < 16 ? N3J : 16 - 4 * N3J, c3 = fi < 16 ? N3J * fi : 16 * N3J + (fi - 16) * n3;
  const uint4* wslice = reinterpret_cast<const uint4*>(rank ? wi : wr) + min((fi >> 1) * 13312, 131328 - 13312);
  auto fetch_rows = [&](int i0, int n) {
#pragma unroll 1
    for (int i = i0; i < i0 + n; ++i) {
      const bf16* xr = x + (size_t)k1_row(cta, i) * 1024;
      const uint32_t rb = bars + 8 * (i < 4 ? B_RAW : B_RAW2);
      if ((i & 3) == 0) mbar_expect_tx(rb, 16384);
      bulk_g2s(stg + i * STG_STRIDE, xr, 2048, rb); bulk_g2s(stg + i * STG_STRIDE + 2048, xr + 1024 * 1024, 2048, rb);
    }
  };
  TSW(0, 31);
  if (tid == 256) {
#pragma unroll
    for (int s = 0; s < 4; ++s) { mbar_init(bars + 8 * (B_FULL + s), 1); mbar_init(bars + 8 * (B_EMPTY + s), 16); }
#pragma unroll
    for (int s = B_WMD; s <= B_UD; ++s) mbar_init(bars + 8 * s, s == B_WMD ? 8 : 2);
#pragma unroll
    for (int s = B_LN; s < B_H + 4; ++s) mbar_init(bars + 8 * s, 8);
#pragma unroll
    for (int s = B_HRDY; s < B_XCH + 16; ++s) mbar_init(bars + 8 * s, 1);
#pragma unroll
    for (int s = 0; s < 16; ++s) mbar_expect_tx(bars + 8 * (B_XCH + s), 2048);
    asm volatile("fence.mbarrier_init.release.cluster;" ::: "memory");
    asm volatile("fence.proxy.async.shared::cta;" ::: "memory");
  }
  __syncwarp();
  cluster_arrive();

  if (UWARP >= 8) {
    reg_dec<56>();
    const int warp = UWARP;
    if (warp == 8 && !is_fft && elect_one()) {
      prefetch_tmap(&maps.wgu3[0]); prefetch_tmap(&maps.wgu3[1]);
      mbar_expect_tx(bars + 8 * B_FULL, ST1);
      tma_2d(sbase, &maps.x, 0, mblk1 * 128, bars + 8 * B_FULL);
      tma_3d(sbase + 16384, &maps.wgu3[0], 0, ngrp1 * 2, bars + 8 * B_FULL); tma_3d(sbase + 32768, &maps.wgu3[1], 0, ngrp1 * 2, bars + 8 * B_FULL);
    }
    if (warp == 8 && is_fft && elect_one()) {
      if (cta < 128) fetch_rows(0, 8);
      mbar_expect_tx(bars + 8 * B_WIN, 196608);
      __nanosleep(3000);
#pragma unroll 1
      for (int i = 0; i < 12; ++i, __nanosleep(200)) bulk_g2s(sbase + i * 16384, wslice + i * 1024, 16384, bars + 8 * B_WIN);
    }
    __syncwarp();
    cluster_wait();
    if (warp == 11) {
      if (lane == 0) {
        unsigned int* hs = &g_flags[(FL_H + mblk1 * 4) * 32];
        const unsigned int* hw = &g_flags[(FL_H + mblk * 4) * 32];
        if (!is_fft) {
          mbar_wait(bars + 8 * B_LN, 0);
          signal_flag(&g_flags[FL_LN * 32]);
          wait_flag<64>(&g_flags[FL_LN * 32], 128);
          fence_proxy_async();
          mbar_arrive(bars + 8 * B_XRDY);
          TS(45);
          mbar_wait(bars + 8 * B_UD, 0);
          signal_flag(&g_flags[FL_K1 * 32]);
#pragma unroll 1
          for (int r = 0; r < 3; ++r) { mbar_wait(bars + 8 * (B_H + r), 0); signal_flag(hs + r * 32); }
        } else {
          if (cta < 128) {
            mbar_wait(bars + 8 * B_LN, 0);
            signal_flag(&g_flags[FL_LN * 32]);
            TS(44);
          }
          mbar_wait(bars + 8 * B_WMD, 0);
          signal_flag(&g_flags[FL_WM * 32]);
          if (cta < 128) {
            mbar_wait(bars + 8 * B_UD, 0);
            signal_flag(&g_flags[FL_K1 * 32]);
          }
          wait_flag<32>(&g_flags[FL_WM * 32], NFFT);
          uint32_t e;
          asm volatile("ld.relaxed.gpu.global.u32 %0, [%1];" : "=r"(e) : "l"(&g_flags[FL_WMAX * 32]) : "memory");
          sts32(bars + WEXP_OFF, min(max(e >> 7, 1u), 252u));
          mbar_arrive(bars + 8 * B_WGO);
          wait_flag<32>(&g_flags[FL_K1 * 32], 128);
          mbar_arrive(bars + 8 * B_URDY);
          TS(46);
          mbar_wait(bars + 8 * B_K2D, 0);
          signal_flag(&g_flags[FL_K2 * 32]);
          wait_flag<32>(&g_flags[FL_K2 * 32], NFFT);
          mbar_arrive(bars + 8 * B_VGO);
          if (cta >= 128) { mbar_wait(bars + 8 * B_K3D, 0); signal_flag(&g_flags[FL_K3 * 32]); }
        }
        if (cta < 128) {
#pragma unroll 1
          for (int r = 0; r < 5; ++r) {
            if (r == 3 && !is_fft) { mbar_wait(bars + 8 * (B_H + 3), 0); signal_flag(hs + 3 * 32); }
            if (r == 2 && is_fft) { mbar_wait(bars + 8 * B_K3D, 0); signal_flag(&g_flags[FL_K3 * 32]); }
            wait_flag<64>(r < 4 ? hw + r * 32 : &g_flags[FL_K3 * 32], r < 4 ? 7 : NFFT);
            fence_proxy_async();
            mbar_arrive(bars + 8 * (B_HRDY + r));
          }
          unsigned int old;
          asm volatile("atom.relaxed.gpu.global.add.u32 %0, [%1], 1;" : "=r"(old) : "l"(&g_flags[FL_DONE * 32]) : "memory");
          if (old == 127) {
#pragma unroll 1
            for (int i = 0; i < FL_COUNT; ++i) g_flags[i * 32] = 0;
          }
        }
      }
    } else {
      if (warp > 8 && cta < 128) {
        const int ht = tid - 288;
        if (!is_fft) {
          mbar_wait(bars + 8 * (B_FULL + 2), 0);
          cs_partial(ht < 32 ? wgate : wup, mblk1, ngrp1, ht);
          __syncwarp();
          if (lane == 0) { signal_flag(&g_flags[(FL_CS + ngrp1) * 32]); wait_flag<100>(&g_flags[(FL_CS + ngrp1) * 32], 32); }
          __syncwarp();
          cs_total(ngrp1, ht, bars + CS_OFF);
          warp_arrive(bars + 8 * B_CRDY, lane);
          TSW(9, 47);
        }
        mbar_wait(bars + 8 * B_K1ST, 0);
        u_copy(cta, ht, stg);
        warp_arrive(bars + 8 * B_UD, lane);
        TSW(9, 50);
      }
      if (is_fft) {
        if (warp == 8) {
          if (cta < 128) mbar_wait(bars + 8 * B_UD, 0);
          if (elect_one()) {
            asm volatile("fence.proxy.async.shared::cta;" ::: "memory");
            mbar_expect_tx(bars + 8 * F_TB, 16384);
            bulk_g2s(sbase + TAB2, g_tab + TAB_B2 * 128, 4096, bars + 8 * F_TB);
            bulk_g2s(sbase + TAB2 + 4096, g_tab + (TAB_A2_0 + rank * TAB_PAR_STRIDE) * 128, 12288, bars + 8 * F_TB);
          }
          __syncwarp();
          mbar_wait(bars + 8 * B_K2D, 0);
          if (elect_one()) {
            asm volatile("fence.proxy.async.shared::cta;" ::: "memory");
            mbar_expect_tx(bars + 8 * (F_TB + 1), 9216);
            bulk_g2s(sbase + TAB3, g_tab + TAB_A5 * 128, 9216, bars + 8 * (F_TB + 1));
          }
          __syncwarp();
          mbar_wait(bars + 8 * B_VGO, 0);
          if (elect_one()) {
            fence_proxy_async();
#pragma unroll 1
            for (int n = 0; n < n3; ++n) {
              const uint32_t vb = bars + 8 * (F_VT + (n & 1)), dst = sbase + (n & 1) * VBUF;
              if (n >= 2) mbar_wait(bars + 8 * (F_C3 + (n & 1)), ((n >> 1) & 1) ^ 1);
              asm volatile("fence.proxy.async.shared::cta;" ::: "memory");
              mbar_expect_tx(vb, 65536 + 2048);
#pragma unroll 1
              for (int G = 0; G < 8; ++G)
                asm volatile("cp.async.bulk.tensor.5d.shared::cluster.global.mbarrier::complete_tx::bytes [%0], [%1, {%3, %6, %4, %6, %5}], [%2];"
                             ::"r"(dst + G * 8192), "l"(&maps.v), "r"(vb), "r"((c3 + n) * 32), "r"((G >> 2) * 17 + (G & 2) * 4), "r"((G & 1) * 2), "r"(0) : "memory");
              asm volatile("cp.async.bulk.tensor.5d.shared::cluster.global.mbarrier::complete_tx::bytes [%0], [%1, {%3, %4, %4, %4, %4}], [%2];"
                           ::"r"(dst + 65536), "l"(&maps.v16), "r"(vb), "r"((c3 + n) * 32), "r"(0) : "memory");
            }
          }
          __syncwarp();
        }
        mbar_wait(bars + 8 * B_K3D, 0);
        asm volatile("fence.proxy.async.shared::cta;" ::: "memory");
      }
      if (cta < 128 && elect_one()) {
        if (warp == 8) {
          if (!is_fft) {
            const CUtensorMap* bm = &maps.wgu3[rank];
            const uint32_t boff = 16384 + rank * 16384;
            int fb0 = ngrp1 * 2;
#pragma unroll 1
            for (int it = 1; it < 64; ++it) {
              const int k0 = (it & 15) * 64;
              const uint32_t fb = bars + 8 * (B_FULL + (it & 3)), sa = sbase + (it & 3) * ST1;
              if (k0 == 0) fb0 += 14;
              if (it >= 4) mbar_wait(fb + 8 * (B_EMPTY - B_FULL), ((it >> 2) & 1) ^ 1);
              mbar_expect_tx(fb, ST1);
              tma_3d_mc(sa + boff, bm, k0, fb0, fb);
              if (it == 3) prefetch_tmap(&maps.xn);
              if (it == 3 || it == 4 || it == 7 || it == 8) fetch_rows(((it - 3) & 1) * 2 + (it > 4) * 4, 2);
              if (it == 16) { TS(32); mbar_wait(bars + 8 * B_XRDY, 0); TS(33); }
              tma_2d(sa, it < 16 ? &maps.x : &maps.xn, k0, mblk1 * 128, fb);
            }
          }
          mbar_arrive(bars + 8 * B_GO);
          prefetch_tmap(&maps.h); prefetch_tmap(&maps.s); prefetch_tmap(&maps.out);
          int rd = 0;
#pragma unroll 1
          for (int i = 0; i < 30; ++i) {
            const uint32_t fb = bars + 8 * (B_FULL + (i & 3)), sa = sbase + (i & 3) * ST1;
            mbar_wait(fb + 8 * (B_EMPTY - B_FULL), ((i >> 2) & 1) ^ 1);
            if (i < 28) {
              mbar_expect_tx(fb, ST1);
              if (i == 7 * rd) { mbar_wait(bars + 8 * (B_HRDY + rd), 0); ++rd; }
              tma_2d(sa, &maps.h, g2_block(i, rank) * 64, mblk * 128, fb);
            } else {
              if (i == 28) {
                mbar_expect_tx(fb, ST1);
                tma_2d(sa, &maps.x, ngrp * 128, mblk * 128, fb); tma_2d(sa + 16384, &maps.x, ngrp * 128 + 64, mblk * 128, fb);
                mbar_wait(bars + 8 * B_SRDY, 0);
                tma_2d(sa + 32768, &maps.s, ngrp * 128, mblk * 128, fb);
              } else {
                mbar_expect_tx(fb, 16384);
                tma_2d(sa, &maps.s, ngrp * 128 + 64, mblk * 128, fb);
              }
            }
          }
        } else if (warp == 9) {
          prefetch_tmap(&maps.wd);
          mbar_wait(bars + 8 * B_GO, 0);
#pragma unroll 1
          for (int i = 0; i < 28; ++i) {
            const uint32_t fb = bars + 8 * (B_FULL + (i & 3)), sb = sbase + (i & 3) * ST1 + 16384;
            const int kc = g2_block(i, rank) * 2;
            mbar_wait(fb + 8 * (B_EMPTY - B_FULL), ((i >> 2) & 1) ^ 1);
            tma_5d(sb, &maps.wd, ngrp * 128, kc, fb); tma_5d(sb + 8192, &maps.wd, ngrp * 128 + 64, kc, fb);
            tma_5d(sb + 16384, &maps.wd, (ngrp ^ 1) * 128, kc, fb); tma_5d(sb + 24576, &maps.wd, (ngrp ^ 1) * 128 + 64, kc, fb);
          }
        }
      }
    }
  } else {
    reg_inc<224>();
    const int g = lane >> 2, q = lane & 3;
    cluster_wait();
    TSW(0, 0);
    const int warp = tid >> 5;
    uint32_t rbars = mapa(bars, lane & 1);
    bf16* hrow = g_h + (size_t)(mblk1 * 128 + warp * 16 + g) * 3584 + ngrp1 * 128 + q * 8 - 896;
    const uint64_t da0 = make_desc(sbase + (UWARP >> 2) * 8192, 16, 1024), db0 = make_desc(sbase + 16384, 8192, 1024);
    uint32_t pk[64];
#pragma unroll
    for (int i = 0; i < 64; ++i) pk[i] = 0;
    const int lag = is_fft ? 0 : UWARP >> 2;
    float acc[128];
#pragma unroll 1
    for (int t = 0;; ++t) {
      const int ngroups = t == 4 ? 7 : 4;
      const bool mm = t == 4 || !is_fft;
      if (t == 4) rbars = mapa(bars, rank);
      if (mm) mbar_wait(bars + 8 * B_FULL, 0);
      wgmma_fence();
      wgmma_n256_first(acc, da0, db0);
#pragma unroll 1
      for (int grp = mm ? 0 : (cta < 128 ? 1 : 4); grp < ngroups; ++grp) {
        const int eg = grp - (t == 1);
        const bool epi = (unsigned)eg < 2u && t > 0 && !is_fft;
        const int code = t * 8 + grp - lag;
#pragma unroll
        for (int s = 0; s < 4; ++s) {
          if (mm) {
            mbar_wait(bars + 8 * (B_FULL + s), grp & 1);
            if (s == 0 && grp == 0) { TSW(0, t == 4 ? 15 : 2 + 5 * t); }
            if (s == 0 && grp == 2 && t != 3) { TSW(0, t == 4 ? 16 : 3 + 5 * t); }
            if (t == 0 && (grp == 1 || grp == 2)) { TSW(0, 36 + (grp - 1) * 4 + s); }
            wgmma_fence();
#pragma unroll
            for (int kk = 0; kk < 4; ++kk)
              if ((s | kk) != 0 || grp != 0) wgmma_n256(acc, da0 + (s * (ST1 >> 4) + kk * 2), db0 + (s * (ST1 >> 4) + kk * 128));
            wgmma_commit();
            wgmma_wait<1>();
            if (lane < 2 && (s > 0 || grp > 0)) mbar_arrive_remote(rbars + 8 * (B_EMPTY + ((s + 3) & 3)));
          }
#define LNP(P) ln_piece<P>(pk, k1_row(cta, warp) * 256 + q * 8 + g, lane, bars, stg + warp * STG_STRIDE + q * 64 + g * 8)
          if (epi) epi_chunk(pk, s, hrow + eg * 64);
          else if (code == 1) { if (s == 0) { LNP(0); LNP(10); } if (s == 1) LNP(11); if (s == 2) { LNP(8); LNP(9); } if (s == 3) { LNP(2); LNP(3); } }
          else if (code == 2) {
            if (s == 0) { LNP(4); LNP(5); }
            if (s == 1) { LNP(6); LNP(7); }
            if (s == 2) {
#pragma unroll
              for (int i = 0; i < 32; ++i) pk[i] = pk[i + 32];
#pragma unroll
              for (int i = 0; i < 4; ++i) {
                const uint4 a = __ldg(reinterpret_cast<const uint4*>(g_tab) + (TAB_A1 + i) * 32 + lane);
                pk[32 + 4 * i] = a.x; pk[33 + 4 * i] = a.y; pk[34 + 4 * i] = a.z; pk[35 + 4 * i] = a.w;
              }
            }
          }
          if (s == 3 && t == 0 && grp == 3 && mm) {
            mbar_wait(bars + 8 * B_XRDY, 0);
            pk[48] = __ldcg(g_st + mblk1 * 128 + warp * 16 + g); pk[49] = __ldcg(g_st + mblk1 * 128 + warp * 16 + g + 8);
          }
        }
        if (epi) {
#pragma unroll
          for (int i = 0; i < 32; ++i) pk[i] = pk[i + 32];
          if (eg == 1) warp_arrive(bars + 8 * (B_H + t - 1), lane);
        }
      }
      if (t == 4) {
        TSW(0, 21);
        const int lr = warp * 16 + (lane & 7) + ((lane >> 3) & 1) * 8;
        uint32_t lbase = sbase + lr * 128;
        uint32_t xch = stg + warp * 4096 + lane * 16;
        const uint32_t rxch = mapa(xch, rank ^ 1), rxb = mapa(bars + 8 * (B_XCH + 2 * warp), rank ^ 1);
        mbar_wait(bars + 8 * B_SRDY, 0);
        wgmma_wait<0>();
        TSW(0, 22);
#pragma unroll
        for (int jp = 0; jp < 8; ++jp)
          asm volatile("st.async.shared::cluster.mbarrier::complete_tx::bytes.v4.b32 [%0], {%1,%2,%3,%4}, [%5];"
                       ::"r"(rxch + jp * 512), "r"(pack_bf16(acc[64 + 8 * jp], acc[65 + 8 * jp])), "r"(pack_bf16(acc[66 + 8 * jp], acc[67 + 8 * jp])),
                         "r"(pack_bf16(acc[68 + 8 * jp], acc[69 + 8 * jp])), "r"(pack_bf16(acc[70 + 8 * jp], acc[71 + 8 * jp])), "r"(rxb + (jp >> 2) * 8) : "memory");
        TSW(0, 24);
#pragma unroll 1
        for (int hf = 0; hf < 2; ++hf) {
          uint32_t xr[16], sr[16], o[16];
          mbar_wait(bars + 8 * (B_FULL + hf), 1);
#pragma unroll
          for (int jp = 0; jp < 4; ++jp) {
            const uint32_t a = lbase + (((jp * 2 + (lane >> 4)) ^ (lane & 7)) << 4);
            asm volatile("ldmatrix.sync.aligned.m8n8.x4.shared.b16 {%0,%1,%2,%3}, [%4];" : "=r"(xr[4 * jp]), "=r"(xr[4 * jp + 1]), "=r"(xr[4 * jp + 2]), "=r"(xr[4 * jp + 3]) : "r"(a) : "memory");
            asm volatile("ldmatrix.sync.aligned.m8n8.x4.shared.b16 {%0,%1,%2,%3}, [%4];" : "=r"(sr[4 * jp]), "=r"(sr[4 * jp + 1]), "=r"(sr[4 * jp + 2]), "=r"(sr[4 * jp + 3]) : "r"(a + 32768) : "memory");
          }
          mbar_wait(bars + 8 * (B_XCH + 2 * warp + hf), 0);
          if (hf == 0) { TSW(0, 20); }
          uint4 pv[4];
#pragma unroll
          for (int jp = 0; jp < 4; ++jp) pv[jp] = lds128(xch + jp * 512);
#pragma unroll
          for (int r = 0; r < 16; ++r) {
            const uint32_t pr = (r & 3) == 0 ? pv[r >> 2].x : (r & 3) == 1 ? pv[r >> 2].y : (r & 3) == 2 ? pv[r >> 2].z : pv[r >> 2].w;
            const float h0 = acc[2 * r] + bf_lo(pr), h1 = acc[2 * r + 1] + bf_hi(pr);
            float t0, t1;
            asm("tanh.approx.f32 %0, %1;" : "=f"(t0) : "f"(h0));
            asm("tanh.approx.f32 %0, %1;" : "=f"(t1) : "f"(h1));
            asm("fma.rn.bf16x2 %0, %1, %2, %3;" : "=r"(o[r]) : "r"(sr[r]), "r"(pack_bf16(fmaf(h0, t0, h0), fmaf(h1, t1, h1))), "r"(xr[r]));
          }
#pragma unroll
          for (int jp = 0; jp < 4; ++jp)
            asm volatile("stmatrix.sync.aligned.m8n8.x4.shared.b16 [%0], {%1,%2,%3,%4};"
                         ::"r"(lbase + (((jp * 2 + (lane >> 4)) ^ (lane & 7)) << 4)), "r"(o[4 * jp]), "r"(o[4 * jp + 1]), "r"(o[4 * jp + 2]), "r"(o[4 * jp + 3]) : "memory");
          asm volatile("fence.proxy.async.shared::cta;" ::: "memory");
          __syncwarp();
          if (elect_one()) {
            tma_store_2d(&maps.out, sbase + hf * 16384 + warp * 2048, ngrp * 128 + hf * 64, mblk * 128 + warp * 16);
            asm volatile("cp.async.bulk.commit_group;" ::: "memory");
          }
#pragma unroll
          for (int i = 0; i < 32; ++i) acc[i] = acc[i + 32];
          lbase += 16384; xch += 2048;
        }
        TSW(0, 23);
        asm volatile("cp.async.bulk.wait_group.read 0;" ::: "memory");
        __syncwarp();
        break;
      }
      wgmma_commit();
      wgmma_wait<0>();
      TSW(0, 4 + 5 * t);
      hrow += 896;
      if (lane < 2 && mm) mbar_arrive_remote(rbars + 8 * (B_EMPTY + 3));
      if (t == 0) {
        if (!is_fft) {
          mbar_wait(bars + 8 * B_CRDY, 0);
          const float m0 = -bf_lo(pk[48]), m1 = -bf_lo(pk[49]);
          float r0, r1;
          asm("rcp.approx.ftz.f32 %0, %1;" : "=f"(r0) : "f"(bf_hi(pk[48])));
          asm("rcp.approx.ftz.f32 %0, %1;" : "=f"(r1) : "f"(bf_hi(pk[49])));
#pragma unroll
          for (int pc = 0; pc < 4; ++pc) {
            ln_fix(acc, pc, bars + CS_OFF + q * 16, m0, m1, r0, r1);
            SCHED_FENCE;
          }
        }
        TSW(0, 26);
        pack_acc<16, 12, 4>(acc, pk);
        SCHED_FENCE;
        uint32_t u[48];
#pragma unroll
        for (int i = 16; i < 48; ++i) asm volatile("or.b32 %0, %1, %2;" : "=r"(u[i]) : "r"(pk[i]), "r"(zero));
        pack_acc<16, 4, 8>(acc, pk);
        SCHED_FENCE;
#pragma unroll
        for (int i = 0; i < 16; ++i) asm volatile("or.b32 %0, %1, %2;" : "=r"(u[i]) : "r"(pk[i]), "r"(zero));
        pack_acc<16, 0, 4>(acc, pk);
        if (cta < 128) {
          k1_fft(u, warp, lane, stg);
          warp_arrive(bars + 8 * B_K1ST, lane);
        }
        TSW(0, 1);
        if (is_fft) {
          {
            const int warp = UWARP;
            w_max(wslice, sbase, bars + 8 * B_WIN, tid);
            warp_arrive(bars + 8 * B_WMD, lane);
            TSW(0, 53);
      {
        const int col0 = 52 * (fi >> 1) - rank;
        {
          const int col = min(col0 + 2 * min(lane, 25), 512 - rank);
          const bool act = lane < 26 && col0 + 2 * lane <= 512;
          uint32_t wa[2][2][8], wc[2][2][8];
#pragma unroll 1
          for (int hf = 0; hf < 4; ++hf) {
            w_fetch(wr, wi, rank, col, warp, 2 * hf, wa, wc);
            if (hf == 0) { mbar_wait(bars + 8 * B_WGO, 0); TSW(0, 51); }
            if (act) w_store(col, sbase + 2 * lane * WCOL + warp * 512 + hf * 128, __uint_as_float((253u - lds32(bars + WEXP_OFF)) << 23), wa, wc);
            __syncwarp();
          }
        }
        asm volatile("bar.sync 1, 256;" ::: "memory");
        TSW(0, 52);
        mbar_wait(bars + 8 * F_TB, 0);
        mbar_wait(bars + 8 * B_URDY, 0);
        TSW(0, 5);
        uint32_t tb2 = sbase + TAB2 + lane * 16;
        asm volatile("" : "+r"(tb2));
        const int jend = min(52, 513 - col0);
        int j = warp + (col0 + warp < 0 ? 8 : 0);
        uint32_t nx[32];
        k2_load(rank, slot_of_col(col0 + j), lane, nx);
#pragma unroll 1
        for (; j < jend; j += 8) {
          uint32_t u[32];
#pragma unroll
          for (int i = 0; i < 32; ++i) u[i] = nx[i];
          if (j + 8 < jend) k2_load(rank, slot_of_col(col0 + j + 8), lane, nx);
          k2_task(rank, slot_of_col(col0 + j), lane, sbase + j * WCOL, tb2, u);
        }
        warp_arrive(bars + 8 * B_K2D, lane);
      }
      TSW(0, 6);
      {
        const float sc = __uint_as_float((lds32(bars + WEXP_OFF) + 1u) << 23);
        const uint32_t off = lane * 64 + ((((warp >> 1) ^ (lane >> 1)) & 3) << 4) + (warp & 1) * 8;
        mbar_wait(bars + 8 * (F_TB + 1), 0);
        uint32_t tb3 = sbase + TAB3 + lane * 16;
        asm volatile("" : "+r"(tb3));
#pragma unroll 1
        for (int n = 0; n < n3; ++n) {
          const uint32_t src = sbase + (n & 1) * VBUF + off;
          mbar_wait(bars + 8 * (F_VT + (n & 1)), (n >> 1) & 1);
          if (n == 0) { TSW(0, 10); }
          uint4 d[2][9];
#pragma unroll
          for (int G = 0; G < 9; ++G) {
            uint2 v[4];
#pragma unroll
            for (int i = 0; i < 4; ++i) {
              v[i] = make_uint2(0, 0);
              const bool ok = G == 8 ? lane < 8 : ((G & 3) != 1 || lane >= 4 || (i == 3 && lane == 3));
              if (ok) v[i] = lds64(src + G * 8192 + i * (G == 8 ? 512 : 2048));
            }
            d[0][G] = make_uint4(__byte_perm(v[0].x, v[1].x, 0x5410), __byte_perm(v[2].x, v[3].x, 0x5410), __byte_perm(v[0].y, v[1].y, 0x5410), __byte_perm(v[2].y, v[3].y, 0x5410));
            d[1][G] = make_uint4(__byte_perm(v[0].x, v[1].x, 0x7632), __byte_perm(v[2].x, v[3].x, 0x7632), __byte_perm(v[0].y, v[1].y, 0x7632), __byte_perm(v[2].y, v[3].y, 0x7632));
          }
          warp_arrive(bars + 8 * (F_C3 + (n & 1)), lane);
#pragma unroll 1
          for (int e = 0; e < 2; ++e) {
            asm volatile("cp.async.bulk.wait_group.read 1;" ::: "memory");
            __syncwarp();
            k3_task(2 * (c3 + n) + (warp >> 2), (warp & 3) * 2 + e, lane, d[0], sbase + SOUT + (warp * 2 + e) * 4096, tb3, sc);
#pragma unroll
            for (int G = 0; G < 9; ++G) d[0][G] = d[1][G];
          }
        }
        asm volatile("cp.async.bulk.wait_group 0;" ::: "memory");
        warp_arrive(bars + 8 * B_K3D, lane);
      }
      TSW(0, 11);
              }
          if (cta >= 128) break;
          t = 3;
#pragma unroll
          for (int i = 0; i < 64; ++i) pk[i] = 0;
        }
      } else {
        pack_acc<16, 0, 16>(acc, pk);
      }
    }
    TSW(0, 25);
  }
}

typedef CUresult (*PFN_encodeTiled)(CUtensorMap*, CUtensorMapDataType, cuuint32_t, void*, const cuuint64_t*, const cuuint64_t*, const cuuint32_t*,
                                    const cuuint32_t*, CUtensorMapInterleave, CUtensorMapSwizzle, CUtensorMapL2promotion, CUtensorMapFloatOOBfill);

static void encode(PFN_encodeTiled enc, CUtensorMap* m, const void* ptr, int rank, const cuuint64_t* dims, const cuuint64_t* strides, const cuuint32_t* box, bool plain = false) {
  cuuint32_t es[5] = {1, 1, 1, 1, 1};
  enc(m, CU_TENSOR_MAP_DATA_TYPE_BFLOAT16, rank, const_cast<void*>(ptr), dims, strides, box, es, CU_TENSOR_MAP_INTERLEAVE_NONE,
      plain ? CU_TENSOR_MAP_SWIZZLE_64B : CU_TENSOR_MAP_SWIZZLE_128B, plain ? CU_TENSOR_MAP_L2_PROMOTION_NONE : CU_TENSOR_MAP_L2_PROMOTION_L2_256B,
      CU_TENSOR_MAP_FLOAT_OOB_FILL_NONE);
}
static void encode2d(PFN_encodeTiled enc, CUtensorMap* m, const void* ptr, cuuint64_t inner, cuuint64_t outer, cuuint32_t box_rows) {
  cuuint64_t dims[2] = {inner, outer}, strides[1] = {inner * 2};
  cuuint32_t box[2] = {64, box_rows};
  encode(enc, m, ptr, 2, dims, strides, box);
}

extern "C" void kernel_launch(void* const* d_in, const int* in_sizes, int n_in, void* d_out, int out_size) {
  (void)in_sizes; (void)n_in; (void)out_size;
  void* fn = nullptr;
  cudaDriverEntryPointQueryResult qr;
  cudaGetDriverEntryPoint("cuTensorMapEncodeTiled", &fn, cudaEnableDefault, &qr);
  PFN_encodeTiled enc = (PFN_encodeTiled)fn;
  void *p_xn, *p_h, *p_s;
  cudaGetSymbolAddress(&p_xn, g_xn); cudaGetSymbolAddress(&p_h, g_h); cudaGetSymbolAddress(&p_s, g_s);
  Maps maps;
  encode2d(enc, &maps.xn, p_xn, 1024, 2048, 128);
  for (int i = 0; i < 2; ++i) {
    cuuint64_t dims[3] = {64, 1024, 56}, strides[2] = {3584 * 2, 128};
    cuuint32_t box[3] = {64, 64, 2};
    encode(enc, &maps.wgu3[i], d_in[4 + i], 3, dims, strides, box);
  }
  encode2d(enc, &maps.h, p_h, 3584, 2048, 128);
  {
    cuuint64_t dims[5] = {1024, 2, 4, 4, 112}, strides[4] = {2048, 8 * 2048, 2 * 2048, 32 * 2048};
    cuuint32_t box[5] = {64, 2, 4, 4, 2};
    encode(enc, &maps.wd, d_in[6], 5, dims, strides, box);
  }
  {
    void* p_v;
    cudaGetSymbolAddress(&p_v, g_V);
    cuuint64_t dims[5] = {2048, 4, 34, 2, 4}, strides[4] = {2 * 4096, 32 * 4096, 4096, 8 * 4096};
    cuuint32_t box[5] = {32, 4, 8, 2, 2};
    encode(enc, &maps.v, p_v, 5, dims, strides, box, true);
    cuuint64_t dims2[5] = {2048, 4, 2, 2, 2}, strides2[4] = {2 * 4096, (cuuint64_t)VSLOT * 4096, 4096, 8 * 4096};
    cuuint32_t box2[5] = {32, 4, 2, 2, 2};
    encode(enc, &maps.v16, (char*)p_v + 512 * 4096, 5, dims2, strides2, box2, true);
  }
  encode2d(enc, &maps.x, d_in[0], 1024, 2048, 128);
  encode2d(enc, &maps.s, p_s, 1024, 2048, 128);
  encode2d(enc, &maps.out, d_out, 1024, 2048, 16);
  cudaFuncSetAttribute(fused_kernel, cudaFuncAttributeMaxDynamicSharedMemorySize, SMEM_BYTES);
  fused_kernel<<<NCTA, 384, SMEM_BYTES>>>(maps, (const bf16*)d_in[0], (const unsigned short*)d_in[1], (const unsigned short*)d_in[2],
                                          (const bf16*)d_in[4], (const bf16*)d_in[5], 0u);
}
```
